```python
import torch

def _softmax(x, axis=-1):
    return torch.softmax(x, dim=axis)
def _gelu(x):
    return torch.nn.functional.gelu(x, approximate="tanh")
def _silu(x):
    return torch.nn.functional.silu(x)
def _sigmoid(x):
    return torch.sigmoid(x)
def _layernorm(x, axis=-1, eps=1e-5):
    m = x.mean(dim=axis, keepdim=True)
    v = x.var(dim=axis, keepdim=True, unbiased=False)
    return (x - m) / torch.sqrt(v + eps)
def _scatter_add(tgt, idx, src, axis=0):
    return tgt.clone().index_add_(axis, idx, src)
def _segment_sum(src, seg, n):
    out = torch.zeros((n,) + src.shape[1:], dtype=src.dtype)
    return out.index_add_(0, seg, src)
def _pad(x, pw):
    flat = tuple(v for pair in reversed(pw) for v in pair)
    return torch.nn.functional.pad(x, flat)

kernel_name = 'standalone__gqa_block_cached__sampling'

def setup_inputs():

    _w = (lambda a: (lambda t: t.to(torch.bfloat16) if t.is_floating_point() else t)(torch.as_tensor(a)))
    B, Sq, D = 16, 8, 512
    Hq, Hkv, Sk, Dh = 32, 8, 4096, 128
    assert Hq % Hkv == 0, (Hq, Hkv)
    return {
        "x": _w((lambda *s: torch.randn(*s, dtype=torch.bfloat16) * 0.8)(B, Sq, D)),
        "k_cache": _w((lambda *s: torch.randn(*s, dtype=torch.bfloat16) * 0.8)(B, Hkv, Sk, Dh)),
        "v_cache": _w((lambda *s: torch.randn(*s, dtype=torch.bfloat16) * 0.05)(B, Hkv, Sk, Dh)),
        "wq": _w((lambda *s: torch.randn(*s, dtype=torch.bfloat16) * 0.8)(D, Hq * Dh) * (D ** -0.5)),
        "wo": _w((lambda *s: torch.randn(*s, dtype=torch.bfloat16) * 0.05)(Hq * Dh, D) * ((Hq * Dh) ** -0.5)),
    }

def reference(x, k_cache, v_cache, wq, wo):
    B, Sq, D = x.shape
    Hq, Dh = 32, 128
    Hkv = k_cache.shape[1]
    rep = Hq // Hkv
    q = (lambda x, *d: x.permute(*d))((x @ wq).reshape(B, Sq, Hq, Dh), 0, 2, 1, 3)
    k = (lambda x, n, axis: torch.repeat_interleave(x, n, dim=axis))(k_cache, rep, axis=1)
    v = (lambda x, n, axis: torch.repeat_interleave(x, n, dim=axis))(v_cache, rep, axis=1)
    scores = torch.einsum("bhqd,bhkd->bhqk", q, k) * (Dh ** -0.5)
    p = _softmax(scores, axis=-1)
    o = torch.einsum("bhqk,bhkd->bhqd", p, v)
    return (lambda x, *d: x.permute(*d))(o, 0, 2, 1, 3).reshape(B, Sq, Hq * Dh) @ wo
```

```cpp
#include <cuda_runtime.h>
#include <cuda_bf16.h>
#include <cuda.h>
#include <stdint.h>

namespace {

constexpr int kCtas = 128;
constexpr int kThreads = 384;
constexpr int kInitThreads = 352;
constexpr int kSlots = 14;
constexpr int kSlotBytes = 16384;
constexpr int kPairs = 32;
constexpr int kHeadSlot = 6;
constexpr int kWoPos = 4 * kPairs;
constexpr int kItems = kWoPos + 4;
constexpr int kSmemBytes = kSlots * kSlotBytes + 1024 + 512 + 1024;
constexpr int kPollLimit = 1 << 16;
constexpr long long kWaitClocks = 1ll << 25;
#define EARLY 3
#define PF_K 0
#define HEAD_DELAY 0
#define X0_DELAY 600
#define X0_PROBE 1
#define PF_WQ 0
#define D_X0 3
#define D_MAIN 4
#define D_TAIL 6
#define TAIL_START 132
#define PACE 1
#define D_MIN 2
#define D_MAX 6
#define GAIN 128
#define PACE_STEP 2
#define PACE_SLEEP 100
#define WO_GATE 1
#define WO_SLACK 48
#define KLEAD 1
#define HINT_AT -1
#define WO_AT 128
#define ARM_AT 8
#define ARM_SPREAD 0
#define X2_MODE 1

struct Scratch {
    uint4 qx[kCtas * 1024];
    uint4 ox[kCtas * 512];
    uint4 px[kCtas * 1024];
    unsigned flag[kCtas * 32];
    unsigned hint[kCtas * 32];
    unsigned epoch[kCtas * 32];
    unsigned progress[2 * 32];
};
__device__ Scratch g_scratch;
#define TRACE(i)
#define TRACE1(i)
#define LAND(i)

__device__ __forceinline__ uint32_t smem_u32(const void* p) { return (uint32_t)__cvta_generic_to_shared(p); }

__device__ __forceinline__ unsigned timer_ns() {
    unsigned long long t;
    asm volatile("mov.u64 %0, %%globaltimer;" : "=l"(t));
    return (unsigned)t;
}
__device__ __forceinline__ bool elect_one() {
    uint32_t p;
    asm volatile("{\n.reg .pred q;\nelect.sync _|q, 0xffffffff;\nselp.u32 %0, 1, 0, q;\n}" : "=r"(p));
    return p != 0;
}
__device__ __forceinline__ void mbar_init(uint32_t bar, int count) {
    asm volatile("mbarrier.init.shared::cta.b64 [%0], %1;" :: "r"(bar), "r"(count) : "memory");
}
__device__ __forceinline__ void mbar_expect_tx(uint32_t bar, int bytes) {
    asm volatile("mbarrier.arrive.expect_tx.shared::cta.b64 _, [%0], %1;" :: "r"(bar), "r"(bytes) : "memory");
}
__device__ __forceinline__ void mbar_arrive(uint32_t bar) {
    asm volatile("mbarrier.arrive.shared::cta.b64 _, [%0];" :: "r"(bar) : "memory");
}
__device__ __forceinline__ bool mbar_try(uint32_t bar, uint32_t parity) {
    uint32_t ok;
    asm volatile("{\n.reg .pred p;\nmbarrier.try_wait.parity.shared::cta.b64 p, [%1], %2;\nselp.u32 %0, 1, 0, p;\n}"
                 : "=r"(ok) : "r"(bar), "r"(parity) : "memory");
    return ok != 0;
}
__device__ __forceinline__ bool mbar_test(uint32_t bar, uint32_t parity) {
    uint32_t ok;
    asm volatile("{\n.reg .pred p;\nmbarrier.test_wait.parity.shared::cta.b64 p, [%1], %2;\nselp.u32 %0, 1, 0, p;\n}"
                 : "=r"(ok) : "r"(bar), "r"(parity) : "memory");
    return ok != 0;
}
__device__ __forceinline__ void mbar_wait(uint32_t bar, uint32_t parity) {
    if (mbar_try(bar, parity)) return;
    const long long t0 = clock64();
    while (!mbar_try(bar, parity))
        if (clock64() - t0 > kWaitClocks) break;
}

__device__ __forceinline__ void tma_2d(uint32_t dst, const CUtensorMap* map, int c0, int c1, uint32_t bar) {
    asm volatile("cp.async.bulk.tensor.2d.shared::cluster.global.mbarrier::complete_tx::bytes [%0], [%1, {%3, %4}], [%2];"
                 :: "r"(dst), "l"(map), "r"(bar), "r"(c0), "r"(c1) : "memory");
}
__device__ __forceinline__ void tma_kv(uint32_t dst, const CUtensorMap* map, int row_group, uint32_t bar, uint64_t policy) {
    asm volatile("cp.async.bulk.tensor.4d.shared::cluster.global.mbarrier::complete_tx::bytes.L2::cache_hint [%0], [%1, {%3, %3, %3, %4}], [%2], %5;"
                 :: "r"(dst), "l"(map), "r"(bar), "r"(0), "r"(row_group), "l"(policy) : "memory");
}
__device__ __forceinline__ void cp_async16(uint32_t dst, const void* src) {
    asm volatile("cp.async.cg.shared.global [%0], [%1], 16;" :: "r"(dst), "l"(src) : "memory");
}
__device__ __forceinline__ void l2_prefetch(const void* p, int bytes) {
    asm volatile("cp.async.bulk.prefetch.L2.global [%0], %1;" :: "l"(p), "r"(bytes) : "memory");
}
__device__ __forceinline__ void map_prefetch(const CUtensorMap* map) {
    asm volatile("prefetch.tensormap [%0];" :: "l"(map) : "memory");
}

__device__ __forceinline__ uint4 ld_gpu(const uint4* p) {
    unsigned long long a, b;
    asm volatile("ld.relaxed.gpu.global.v2.b64 {%0, %1}, [%2];" : "=l"(a), "=l"(b) : "l"(p) : "memory");
    return make_uint4((uint32_t)a, (uint32_t)(a >> 32), (uint32_t)b, (uint32_t)(b >> 32));
}
__device__ __forceinline__ void st_gpu(uint4* p, uint32_t x, uint32_t y, uint32_t z, uint32_t w) {
    const unsigned long long a = (unsigned long long)x | ((unsigned long long)y << 32);
    const unsigned long long b = (unsigned long long)z | ((unsigned long long)w << 32);
    asm volatile("st.relaxed.gpu.global.v2.b64 [%0], {%1, %2};" :: "l"(p), "l"(a), "l"(b) : "memory");
}
__device__ __forceinline__ uint32_t ld_probe(const uint4* p, int word) {
    uint32_t v;
    asm volatile("ld.relaxed.gpu.global.u32 %0, [%1];" : "=r"(v) : "l"(reinterpret_cast<const uint32_t*>(p) + word) : "memory");
    return v;
}
__device__ __forceinline__ void sts128(uint32_t addr, uint32_t x, uint32_t y, uint32_t z, uint32_t w) {
    asm volatile("st.shared.v4.u32 [%0], {%1, %2, %3, %4};" :: "r"(addr), "r"(x), "r"(y), "r"(z), "r"(w) : "memory");
}
__device__ __forceinline__ uint4 lds128(uint32_t addr) {
    uint4 v;
    asm volatile("ld.shared.v4.u32 {%0, %1, %2, %3}, [%4];" : "=r"(v.x), "=r"(v.y), "=r"(v.z), "=r"(v.w) : "r"(addr) : "memory");
    return v;
}
__device__ __forceinline__ uint32_t nonzero(uint32_t w) { return w == 0u ? 0x80000000u : w; }

__device__ __forceinline__ uint32_t pack_bf16(float lo, float hi) {
    uint32_t r;
    asm("cvt.rn.bf16x2.f32 %0, %1, %2;" : "=r"(r) : "f"(hi), "f"(lo));
    return r;
}
__device__ __forceinline__ float ex2(float x) {
    float y;
    asm("ex2.approx.ftz.f32 %0, %1;" : "=f"(y) : "f"(x));
    return y;
}

__device__ __forceinline__ uint64_t make_desc(uint32_t addr, uint32_t lbo_bytes, uint32_t sbo_bytes) {
    return (uint64_t)((addr & 0x3FFFF) >> 4) | ((uint64_t)(lbo_bytes >> 4) << 16) | ((uint64_t)(sbo_bytes >> 4) << 32) | (1ull << 62);
}

__device__ __forceinline__ void wg_fence() { asm volatile("wgmma.fence.sync.aligned;" ::: "memory"); }
__device__ __forceinline__ void wg_commit() { asm volatile("wgmma.commit_group.sync.aligned;" ::: "memory"); }
template <int N> __device__ __forceinline__ void wg_wait() { asm volatile("wgmma.wait_group.sync.aligned %0;" :: "n"(N) : "memory"); }
template <int N> __device__ __forceinline__ void reg_fence(float (&r)[N]) {
#pragma unroll
    for (int i = 0; i < N; i++) asm volatile("" : "+f"(r[i]) :: "memory");
}

#define ACC8(d, o) "+f"(d[o]), "+f"(d[o + 1]), "+f"(d[o + 2]), "+f"(d[o + 3]), "+f"(d[o + 4]), "+f"(d[o + 5]), "+f"(d[o + 6]), "+f"(d[o + 7])
#define ACC32(d, o) ACC8(d, o), ACC8(d, o + 8), ACC8(d, o + 16), ACC8(d, o + 24)
#define REGS32 "{%0, %1, %2, %3, %4, %5, %6, %7, %8, %9, %10, %11, %12, %13, %14, %15, " \
               "%16, %17, %18, %19, %20, %21, %22, %23, %24, %25, %26, %27, %28, %29, %30, %31}"
#define REGS64 "{%0, %1, %2, %3, %4, %5, %6, %7, %8, %9, %10, %11, %12, %13, %14, %15, " \
               "%16, %17, %18, %19, %20, %21, %22, %23, %24, %25, %26, %27, %28, %29, %30, %31, " \
               "%32, %33, %34, %35, %36, %37, %38, %39, %40, %41, %42, %43, %44, %45, %46, %47, " \
               "%48, %49, %50, %51, %52, %53, %54, %55, %56, %57, %58, %59, %60, %61, %62, %63}"

__device__ __forceinline__ void mma_n64_ss_bt(float (&d)[32], uint64_t da, uint64_t db, int accumulate) {
    asm volatile("{\n.reg .pred p;\nsetp.ne.b32 p, %34, 0;\n"
                 "wgmma.mma_async.sync.aligned.m64n64k16.f32.bf16.bf16 " REGS32 ", %32, %33, p, 1, 1, 0, 1;\n}"
                 : ACC32(d, 0) : "l"(da), "l"(db), "r"(accumulate));
}
template <int TB>
__device__ __forceinline__ void mma_n64_rs(float (&d)[32], const uint32_t* a, uint64_t db, int accumulate) {
    asm volatile("{\n.reg .pred p;\nsetp.ne.b32 p, %37, 0;\n"
                 "wgmma.mma_async.sync.aligned.m64n64k16.f32.bf16.bf16 " REGS32 ", {%32, %33, %34, %35}, %36, p, 1, 1, %38;\n}"
                 : ACC32(d, 0) : "r"(a[0]), "r"(a[1]), "r"(a[2]), "r"(a[3]), "l"(db), "r"(accumulate), "n"(TB));
}
__device__ __forceinline__ void mma_n128_rs_bt(float (&d)[64], const uint32_t* a, uint64_t db) {
    asm volatile("{\n.reg .pred p;\nsetp.ne.b32 p, 1, 0;\n"
                 "wgmma.mma_async.sync.aligned.m64n128k16.f32.bf16.bf16 " REGS64 ", {%64, %65, %66, %67}, %68, p, 1, 1, 1;\n}"
                 : ACC32(d, 0), ACC32(d, 32) : "r"(a[0]), "r"(a[1]), "r"(a[2]), "r"(a[3]), "l"(db));
}

__device__ __forceinline__ int skip_wo(int n) { return n < WO_AT ? n : n + 4; }
__device__ __forceinline__ int pos_k(int p) { return skip_wo(p == 0 ? 0 : 4 * p - 2); }
__device__ __forceinline__ int pos_v(int p) { return skip_wo(p == 31 ? 126 : 4 * p + 4); }
__device__ __forceinline__ bool item_is_v(int pos) { return pos >= 126 || (pos >= 4 && !(pos & 2)); }
__device__ __forceinline__ int item_tile(int pos) {
    return (pos & 1) + 2 * (pos < 2 ? 0 : pos >= 126 ? 31 : (pos & 2) ? (pos + 2) >> 2 : (pos - 4) >> 2);
}
template <int V> struct Const { static constexpr int value = V; };
template <int N, int I = 0, typename F> __device__ __forceinline__ void static_for(F&& f) {
    if constexpr (I < N) { f(Const<I>{}); static_for<N, I + 1>(f); }
}

struct Ring {
    uint32_t base, full, empty;
    __device__ __forceinline__ uint32_t wait(int pos) const {
        const int slot = pos % kSlots;
        mbar_wait(full + 8 * slot, (pos / kSlots) & 1);
        return base + slot * kSlotBytes;
    }
    __device__ __forceinline__ void release(int pos, int lane) const {
        if (lane == 0) mbar_arrive(empty + 8 * (pos % kSlots));
    }
};

__global__ void __launch_bounds__(kThreads, 1)
gqa_block_kernel(const char* __restrict__ x_raw, const char* __restrict__ wq_raw, const char* __restrict__ k_raw,
                 Scratch* __restrict__ sc, __nv_bfloat16* __restrict__ out,
                 const __grid_constant__ CUtensorMap map_k, const __grid_constant__ CUtensorMap map_v,
                 const __grid_constant__ CUtensorMap map_wo) {
    extern __shared__ char smem_raw[];
    const int cta = blockIdx.x;
    const int warp = __shfl_sync(0xffffffffu, threadIdx.x >> 5, 0), lane = threadIdx.x & 31;
    const int b = cta >> 3, h = cta & 7;
    const int bg = b >> 3, j = b & 7;

    Ring ring;
    ring.base = (smem_u32(smem_raw) + 1023u) & ~1023u;
    ring.full = ring.base + kSlots * kSlotBytes;
    ring.empty = ring.full + 8 * kSlots;
    const uint32_t peers_ready = ring.empty + 8 * kSlots;
    const uint32_t q_ready = peers_ready + 8;
    const uint32_t wo_go = q_ready + 8;
    const uint32_t pace = wo_go + 8;
    const uint32_t stats = ring.full + 512;

    uint64_t stream_policy;
    asm volatile("createpolicy.fractional.L2::evict_first.b64 %0, 1.0;" : "=l"(stream_policy));
    if (warp == 8) {
        if (elect_one()) {
            if (PF_K) l2_prefetch(k_raw + ((size_t)cta << 20), PF_K);
#pragma unroll
            for (int i = 0; i < EARLY; i++) mbar_init(ring.full + 8 * i, 1);
            asm volatile("fence.mbarrier_init.release.cluster;" ::: "memory");
#pragma unroll
            for (int i = 0; i < EARLY; i++) {
                mbar_expect_tx(ring.full + 8 * i, kSlotBytes);
                tma_kv(ring.base + i * kSlotBytes, &map_k, cta * 512 + i * 8, ring.full + 8 * i, stream_policy);
            }
            map_prefetch(&map_v);
#pragma unroll
            for (int i = EARLY; i < kSlots; i++) mbar_init(ring.full + 8 * i, 1);
#pragma unroll
            for (int i = 0; i < kSlots; i++) mbar_init(ring.empty + 8 * i, 4);
            mbar_init(peers_ready, 1);
            mbar_init(q_ready, 4);
            mbar_init(wo_go, 1);
            asm volatile("st.volatile.shared.v2.u32 [%0], {%1, %2};" :: "r"(pace), "r"(D_MAIN), "r"(0) : "memory");
            asm volatile("fence.mbarrier_init.release.cluster;" ::: "memory");
        }
        __syncwarp();
        asm volatile("bar.arrive 1, %0;" :: "n"(kInitThreads) : "memory");
    }

    if (warp >= 8) {
        asm volatile("setmaxnreg.dec.sync.aligned.u32 40;");
        const unsigned epoch = (*(volatile unsigned*)&sc->epoch[cta * 32] + 1u) | 0x80000000u;
        if (warp == 8) {
            if (elect_one()) {

                int slot = EARLY, lap = 0;
                bool started = false;
                for (int pos = EARLY; pos < kItems; pos++) {
                    const int releases = lap + (slot >= kHeadSlot);
                    if (releases > 0) mbar_wait(ring.empty + 8 * slot, (releases - 1) & 1);
                    if (!started) started = mbar_test(q_ready, 0);
                    int depth = D_MAIN;
                    if (PACE) {
                        asm volatile("st.volatile.shared.u32 [%0], %1;" :: "r"(pace + 4), "r"(pos) : "memory");
                        asm volatile("ld.volatile.shared.u32 %0, [%1];" : "=r"(depth) : "r"(pace) : "memory");
                    }
                    if (!started) depth = D_X0;
                    if (pos >= TAIL_START) depth = D_TAIL;
                    if (PACE && WO_GATE && WO_AT == kWoPos && pos >= kWoPos) {
                        if (pos == kWoPos) mbar_wait(wo_go, 0);
                        depth = kSlots;
                    }
                    if (depth < kSlots && pos >= depth) ring.wait(pos - depth);
                    const uint32_t bar = ring.full + 8 * slot, dst = ring.base + slot * kSlotBytes;
                    mbar_expect_tx(bar, kSlotBytes);
                    if (pos < WO_AT || pos >= WO_AT + 4) {
                        const int n = pos < WO_AT ? pos : pos - 4;
                        tma_kv(dst, item_is_v(n) ? &map_v : &map_k, cta * 512 + item_tile(n) * 8, bar, stream_policy);
                        if (pos == 100) map_prefetch(&map_wo);
                    } else {
                        tma_2d(dst, &map_wo, j * 64, h * 512 + (pos - WO_AT) * 128, bar);
                    }
                    if (++slot == kSlots) { slot = 0; lap++; }
                }
            }
        }
        else if (warp == 9) {
            const int peer = (lane & 8) ? b * 8 + (lane & 7) : (bg * 8 + (lane & 7)) * 8 + h;
            asm volatile("bar.sync 1, %0;" :: "n"(kInitThreads) : "memory");
            asm volatile("bar.sync 3, 288;" ::: "memory");
            if (lane == 0) {
                asm volatile("fence.acq_rel.gpu;" ::: "memory");
                asm volatile("st.relaxed.gpu.global.u32 [%0], %1;" :: "l"(&sc->flag[cta * 32]), "r"(epoch) : "memory");
                sc->epoch[cta * 32] = epoch;
                if (cta == 0) sc->progress[((epoch & 1) ^ 1) * 32] = 0;
            }
            __syncwarp();
            unsigned v;
            int it = 0;
            do {
                __nanosleep(500);
                asm volatile("ld.acquire.gpu.global.u32 %0, [%1];" : "=r"(v) : "l"(&sc->flag[peer * 32]) : "memory");
                if (++it > kPollLimit) break;
            } while (v != epoch);
            __syncwarp();
            if (lane == 0) mbar_arrive(peers_ready);
        }
        else if (warp == 11) {
            asm volatile("bar.sync 1, %0;" :: "n"(kInitThreads) : "memory");
            if (PACE && lane == 0) {
                int done = 0, it = 0;
                while (done < kWoPos / PACE_STEP && ++it < kPollLimit) {
                    int pos;
                    asm volatile("ld.volatile.shared.u32 %0, [%1];" : "=r"(pos) : "r"(pace + 4) : "memory");
                    const int now = pos / PACE_STEP;
                    if (now > done) {
                        unsigned seen;
                        asm volatile("atom.relaxed.gpu.global.add.u32 %0, [%1], %2;" : "=r"(seen)
                                     : "l"(&sc->progress[(epoch & 1) * 32]), "r"(now - done) : "memory");
                        const int lag = ((int)seen - 64 - 128 * (now - 1)) * PACE_STEP;
                        const int depth = min(max(D_MAIN + (lag + GAIN / 2 + 64 * GAIN) / GAIN - 64, D_MIN), D_MAX);
                        if (now > 2) asm volatile("st.volatile.shared.u32 [%0], %1;" :: "r"(pace), "r"(depth) : "memory");
                        done = now;
                    } else {
                        __nanosleep(PACE_SLEEP);
                    }
                }
                unsigned total;
                do {
                    asm volatile("ld.relaxed.gpu.global.u32 %0, [%1];" : "=r"(total) : "l"(&sc->progress[(epoch & 1) * 32]) : "memory");
                } while (total < kCtas * (kWoPos / PACE_STEP) - WO_SLACK && ++it < kPollLimit);
                mbar_arrive(wo_go);
            }
        }
    } else {
        TRACE(0);
        const int wg = warp >> 2, wq = warp & 3;
        const int g = lane >> 2, t = lane & 3;
        const bool active = (wq >> 1) == wg;
        const int hp = wq & 1;

        {
            if (HEAD_DELAY) { const long long c0 = clock64(); while (clock64() - c0 < HEAD_DELAY) {} }
            const int tid = threadIdx.x;
            const int xr = tid >> 4, xc = tid & 15, wr = tid >> 3, wc = tid & 7;
            const char* xs = x_raw + (size_t)(bg * 64 + xr) * 1024 + xc * 16;
            const char* ws = wq_raw + (size_t)wr * 8192 + (h * 512 + j * 64) * 2 + wc * 16;
            const uint32_t xd = ring.base + kHeadSlot * kSlotBytes + (xc >> 3) * 8192 + xr * 128 + (((xc ^ xr) & 7) << 4);
            const uint32_t wd = ring.base + (kHeadSlot + 1) * kSlotBytes + wr * 128 + (((wc ^ wr) & 7) << 4);
#pragma unroll
            for (int c = 0; c < 4; c++) {
#pragma unroll
                for (int i = 0; i < 4; i++) {
                    cp_async16(wd + c * 2 * kSlotBytes + i * 4096, ws + (size_t)(c * 128 + i * 32) * 8192);
                    cp_async16(xd + c * 2 * kSlotBytes + i * 2048, xs + i * 16384 + c * 256);
                }
                asm volatile("cp.async.commit_group;" ::: "memory");
            }
        }
        const unsigned epoch = (*(volatile unsigned*)&sc->epoch[cta * 32] + 1u) | 0x80000000u;
        uint4* const qx_dst = sc->qx + (((bg * 8 + 2 * wq) * 8 + h) * 8 + j) * 128 + lane;
        uint4* const ox_mine = sc->ox + cta * 512 + hp * 256 + lane;
        uint4* const px_dst = sc->px + ((b * 8 + 2 * wq) * 8 + h) * 128 + lane;
        if (wg == 0) {
#pragma unroll
            for (int c = 0; c < 8; c++) st_gpu(qx_dst + (c >> 2) * 8192 + (c & 3) * 32, 0, 0, 0, 0);
        }
        asm volatile("setmaxnreg.inc.sync.aligned.u32 232;");
        asm volatile("bar.sync 1, %0;" :: "n"(kInitThreads) : "memory");

        float s[32];
        auto chunk_landed = [&](auto c) {
            asm volatile("cp.async.wait_group %0;" :: "n"(3 - c.value) : "memory");
            asm volatile("fence.proxy.async.shared::cta;" ::: "memory");
        };
        if (wg == 0) {
            static_for<4>([&](auto c) {
                chunk_landed(c);
                asm volatile("bar.sync %0, 256;" :: "n"(5 + c.value) : "memory");
                LAND(c.value);
                const uint32_t xa = ring.base + (kHeadSlot + 2 * c.value) * kSlotBytes, wa = xa + kSlotBytes;
                wg_fence();
#pragma unroll
                for (int ks = 0; ks < 8; ks++)
                    mma_n64_ss_bt(s, make_desc(xa + (ks >> 2) * 8192 + (ks & 3) * 32, 16, 1024),
                                  make_desc(wa + ks * 2048, 16, 1024), c.value | ks);
                wg_commit();
                wg_wait<0>();
                ring.release(kHeadSlot + 2 * c.value, lane);
                ring.release(kHeadSlot + 2 * c.value + 1, lane);
            });
            reg_fence(s);
            TRACE(1);
#pragma unroll
            for (int r = 0; r < 2; r++)
#pragma unroll
                for (int c = 0; c < 4; c++) {
                    const float* a = s + 8 * c + 2 * r;
                    st_gpu(qx_dst + r * 8192 + c * 32, pack_bf16(a[0], a[1]), epoch, pack_bf16(a[4], a[5]), epoch);
                }
            asm volatile("bar.arrive 9, 256;" ::: "memory");
        } else {
            static_for<4>([&](auto c) {
                chunk_landed(c);
                asm volatile("bar.arrive %0, 256;" :: "n"(5 + c.value) : "memory");
            });
            asm volatile("bar.sync 9, 256;" ::: "memory");
        }

        uint32_t qa[32];
#pragma unroll
        for (int i = 0; i < 32; i++) qa[i] = 0;
        if (active) {
            const uint4* src = sc->qx + (cta * 8 + 4 * hp) * 128 + lane;
            int it = 0;
            const uint4* probe = sc->qx + (cta * 8 + 4 * hp + (lane & 3)) * 128 + 127;
            while (!__all_sync(0xffffffffu, lane >= 4 || ld_probe(probe, 3) == epoch))
                if (++it > kPollLimit) break;
            TRACE(9);
            while (true) {
                uint32_t stale = 0;
#pragma unroll
                for (int r = 0; r < 2; r++)
#pragma unroll
                    for (int c = 0; c < 8; c++) {
                        const uint4 v = ld_gpu(src + (r * 8 + c) * 32);
                        qa[4 * c + r] = v.x; qa[4 * c + 2 + r] = v.z;
                        stale |= (v.y ^ epoch) | (v.w ^ epoch);
                    }
                if (__all_sync(0xffffffffu, stale == 0)) break;
                if (++it > kPollLimit) break;
            }
            if (lane == 0) mbar_arrive(q_ready);
        }
        TRACE(2);

        const float kScale = 0.08838834764831845f * 1.4426950408889634f;
        float o[64];
#pragma unroll
        for (int i = 0; i < 64; i++) o[i] = 0.f;
        uint32_t pa[16];
#pragma unroll
        for (int i = 0; i < 16; i++) pa[i] = 0;
        float m0 = -INFINITY, m1 = -INFINITY, l0 = 0.f, l1 = 0.f;

        auto issue_qk = [&](int pos) {
            const uint32_t ka = ring.wait(pos);
            wg_fence();
#pragma unroll
            for (int ks = 0; ks < 8; ks++)
                mma_n64_rs<0>(s, qa + 4 * ks, make_desc(ka + (ks >> 2) * 1024 + (ks & 3) * 32, 16, 2048), ks);
            wg_commit();
        };
        auto hint = [&]() {
            if (warp == 4 && lane == 0)
                asm volatile("st.relaxed.gpu.global.u32 [%0], %1;" :: "l"(&sc->hint[cta * 32]), "r"(epoch) : "memory");
        };
        auto issue_pv = [&](int pos, bool send_hint) {
            const uint32_t va = ring.wait(pos);
            if (send_hint) hint();
            wg_fence();
#pragma unroll
            for (int ks = 0; ks < 4; ks++) mma_n128_rs_bt(o, pa + 4 * ks, make_desc(va + ks * 4096, 1024, 2048));
            wg_commit();
        };
        float alpha0 = 1.f, alpha1 = 1.f;
        auto softmax = [&]() {
            float x0 = fmaxf(s[0], s[1]), x1 = fmaxf(s[2], s[3]);
#pragma unroll
            for (int i = 1; i < 8; i++) {
                x0 = fmaxf(x0, fmaxf(s[4 * i], s[4 * i + 1]));
                x1 = fmaxf(x1, fmaxf(s[4 * i + 2], s[4 * i + 3]));
            }
            x0 = fmaxf(x0, __shfl_xor_sync(0xffffffffu, x0, 1));
            x1 = fmaxf(x1, __shfl_xor_sync(0xffffffffu, x1, 1));
            x0 = fmaxf(x0, __shfl_xor_sync(0xffffffffu, x0, 2));
            x1 = fmaxf(x1, __shfl_xor_sync(0xffffffffu, x1, 2));
            const float n0 = fmaxf(m0, x0), n1 = fmaxf(m1, x1);
            alpha0 = ex2((m0 - n0) * kScale);
            alpha1 = ex2((m1 - n1) * kScale);
            m0 = n0; m1 = n1;
            const float b0 = -n0 * kScale, b1 = -n1 * kScale;
            float r0 = 0.f, r1 = 0.f;
#pragma unroll
            for (int i = 0; i < 8; i++) {
                s[4 * i] = ex2(fmaf(s[4 * i], kScale, b0));
                s[4 * i + 1] = ex2(fmaf(s[4 * i + 1], kScale, b0));
                s[4 * i + 2] = ex2(fmaf(s[4 * i + 2], kScale, b1));
                s[4 * i + 3] = ex2(fmaf(s[4 * i + 3], kScale, b1));
                r0 += s[4 * i] + s[4 * i + 1];
                r1 += s[4 * i + 2] + s[4 * i + 3];
            }
            l0 = fmaf(l0, alpha0, r0);
            l1 = fmaf(l1, alpha1, r1);
        };
        auto rescale_and_pack = [&]() {
#pragma unroll
            for (int i = 0; i < 16; i++) {
                o[4 * i] *= alpha0; o[4 * i + 1] *= alpha0;
                o[4 * i + 2] *= alpha1; o[4 * i + 3] *= alpha1;
                pa[i] = pack_bf16(s[2 * i], s[2 * i + 1]);
            }
        };

        {
            const int pos = wg;
            issue_qk(pos);
            wg_wait<0>();
            reg_fence(s);
            ring.release(pos, lane);
            if (active) { softmax(); rescale_and_pack(); }
        }
        TRACE(3);
        auto arm = [&]() {
            if (wg == 0) {
#pragma unroll
                for (int c = 0; c < 8; c++) st_gpu(px_dst + (c >> 2) * 1024 + (c & 3) * 32, 0, 0, 0, 0);
            } else if (active) {
#pragma unroll
                for (int c = 0; c < 8; c++) st_gpu(ox_mine + c * 32, 0, 0, 0, 0);
            } else if (wq == 0 && lane < 8) {
                sc->hint[cta * 32 + lane] = 0;
            }
            asm volatile("bar.arrive 3, 288;" ::: "memory");
        };
        if (ARM_AT == 0) arm();

        int vpos = pos_v(0) + wg;
#pragma unroll 1
        for (int p = 1; p < kPairs; p++) {
            const int kpos = pos_k(p) + wg;
            issue_qk(kpos);
            issue_pv(vpos, HINT_AT == 0 && p == kPairs - 1);
            wg_wait<1>();
            reg_fence(s);
            ring.release(kpos, lane);
            if (active) softmax();
            wg_wait<0>();
            reg_fence(o);
            ring.release(vpos, lane);
            if (active) rescale_and_pack();
            vpos = pos_v(p) + wg;
            if (ARM_AT > 0 && p == ARM_AT + (ARM_SPREAD ? (cta & 15) : 0)) arm();
        }
        mbar_wait(peers_ready, 0);
        if (HINT_AT == 1) hint();
        issue_pv(vpos, HINT_AT == 2);
        l0 += __shfl_xor_sync(0xffffffffu, l0, 1);
        l1 += __shfl_xor_sync(0xffffffffu, l1, 1);
        l0 += __shfl_xor_sync(0xffffffffu, l0, 2);
        l1 += __shfl_xor_sync(0xffffffffu, l1, 2);

        const uint32_t part = ring.base + (pos_k(kPairs - 1) % kSlots) * kSlotBytes + hp * 8192 + lane * 16;
        const uint32_t part_stats = stats + (hp * 32 + lane) * 16;

        if (wg == 0) {
            wg_wait<0>();
            reg_fence(o);
            if (active) {
                sts128(part_stats, __float_as_uint(m0), __float_as_uint(m1), __float_as_uint(l0), __float_as_uint(l1));
#pragma unroll
                for (int c = 0; c < 16; c++)
                    sts128(part + c * 512, __float_as_uint(o[4 * c]), __float_as_uint(o[4 * c + 1]),
                           __float_as_uint(o[4 * c + 2]), __float_as_uint(o[4 * c + 3]));
                asm volatile("bar.arrive 4, 128;" ::: "memory");
            }
            TRACE(4);

            uint32_t oa[128];
#pragma unroll
            for (int i = 0; i < 128; i++) oa[i] = 0;
            {
                const uint4* src = sc->ox + ((bg * 8 + 2 * wq) * 8 + h) * 512 + lane;
                const uint4* probe = sc->ox + ((bg * 8 + 2 * wq + ((lane >> 1) & 1)) * 8 + h) * 512 + (lane & 1) * 256 + 255;
                uint32_t pending = 3, seen = 0;
                int it = 0;
                while (true) {
                    seen = __ballot_sync(0xffffffffu, lane < 4 && ld_probe(probe, 2) != 0);
                    seen = ((seen & 3) == 3) | ((seen >> 2) == 3) << 1;
#pragma unroll
                    for (int r = 0; r < 2; r++) {
                        if ((pending & seen) >> r & 1) {
                            uint32_t low = 0xffffffffu;
#pragma unroll
                            for (int c = 0; c < 16; c++) {
                                const uint4 v = ld_gpu(src + r * 8 * 512 + c * 32);
                                oa[8 * c + r] = v.x; oa[8 * c + 2 + r] = v.y; oa[8 * c + 4 + r] = v.z; oa[8 * c + 6 + r] = v.w;
                            }
#pragma unroll
                            for (int c = 0; c < 16; c++) low = __vimin3_u32(low, oa[8 * c + r], oa[8 * c + 4 + r]);
                            if (__all_sync(0xffffffffu, low != 0)) pending &= ~(1u << r);
                        }
                    }
                    if (pending == 0) break;
                    if (++it > kPollLimit) break;
                }
            }
            TRACE(6);

#pragma unroll
            for (int c = 0; c < 4; c++) {
                const uint32_t wa = ring.wait(WO_AT + c);
                wg_fence();
#pragma unroll
                for (int ks = 0; ks < 8; ks++)
                    mma_n64_rs<1>(s, oa + 32 * c + 4 * ks, make_desc(wa + ks * 2048, 16, 1024), c | ks);
                wg_commit();
            }
            wg_wait<0>();
            reg_fence(s);
            TRACE(7);
#pragma unroll
            for (int r = 0; r < 2; r++)
#pragma unroll
                for (int c = 0; c < 4; c++) {
                    const float* a = s + 8 * c + 2 * r;
                    st_gpu(px_dst + r * 1024 + c * 32, nonzero(__float_as_uint(a[0])), __float_as_uint(a[1]),
                           nonzero(__float_as_uint(a[4])), __float_as_uint(a[5]));
                }
        } else {
            uint4 other[16];
            float own0 = 0.f, own1 = 0.f, oth0 = 0.f, oth1 = 0.f;
            if (active) {
                asm volatile("bar.sync 4, 128;" ::: "memory");
                const uint4 st = lds128(part_stats);
#pragma unroll
                for (int c = 0; c < 16; c++) other[c] = lds128(part + c * 512);
                const float pm0 = __uint_as_float(st.x), pm1 = __uint_as_float(st.y);
                const float n0 = fmaxf(m0, pm0), n1 = fmaxf(m1, pm1);
                own0 = ex2((m0 - n0) * kScale); oth0 = ex2((pm0 - n0) * kScale);
                own1 = ex2((m1 - n1) * kScale); oth1 = ex2((pm1 - n1) * kScale);
                const float inv0 = 1.f / (l0 * own0 + __uint_as_float(st.z) * oth0);
                const float inv1 = 1.f / (l1 * own1 + __uint_as_float(st.w) * oth1);
                own0 *= inv0; oth0 *= inv0; own1 *= inv1; oth1 *= inv1;
            }
            wg_wait<0>();
            reg_fence(o);
            TRACE1(11);
            if (active) {
#pragma unroll
                for (int c = 0; c < 16; c++) {
                    o[4 * c] = fmaf(o[4 * c], own0, __uint_as_float(other[c].x) * oth0);
                    o[4 * c + 1] = fmaf(o[4 * c + 1], own0, __uint_as_float(other[c].y) * oth0);
                    o[4 * c + 2] = fmaf(o[4 * c + 2], own1, __uint_as_float(other[c].z) * oth1);
                    o[4 * c + 3] = fmaf(o[4 * c + 3], own1, __uint_as_float(other[c].w) * oth1);
                }
#pragma unroll
                for (int r = 0; r < 2; r++)
#pragma unroll
                    for (int c = 0; c < 4; c++) {
                        const float* a = o + 16 * c + 2 * r;
                        st_gpu(ox_mine + (r * 4 + c) * 32, nonzero(pack_bf16(a[0], a[1])), pack_bf16(a[4], a[5]),
                               nonzero(pack_bf16(a[8], a[9])), pack_bf16(a[12], a[13]));
                    }
            }
            TRACE1(5);

            const uint4* src = sc->px + cta * 1024 + wq * 32 + lane;
            uint4 v[8];
            int it = 0;
            const uint4* probe = sc->px + cta * 1024 + (lane & 7) * 128 + wq * 32 + 31;
            while (__popc(__ballot_sync(0xffffffffu, lane < 8 && ld_probe(probe, 2) != 0)) < X2_MODE)
                if (++it > kPollLimit) break;
#pragma unroll
            for (int i = 0; i < 8; i++) v[i] = make_uint4(0, 0, 0, 0);
            while (true) {
                uint32_t low = 0xffffffffu;
#pragma unroll
                for (int i = 0; i < 8; i++) if (v[i].x == 0 || v[i].z == 0) v[i] = ld_gpu(src + i * 128);
#pragma unroll
                for (int i = 0; i < 8; i++) low = __vimin3_u32(low, v[i].x, v[i].z);
                if (low != 0) break;
                if (++it > kPollLimit) break;
            }
            float r0 = 0.f, r1 = 0.f, r2 = 0.f, r3 = 0.f;
#pragma unroll
            for (int i = 0; i < 8; i++) {
                r0 += __uint_as_float(v[i].x); r1 += __uint_as_float(v[i].y);
                r2 += __uint_as_float(v[i].z); r3 += __uint_as_float(v[i].w);
            }
            uint32_t* dst = reinterpret_cast<uint32_t*>(out + ((bg * 8 + h) * 8 + g) * 512 + j * 64 + wq * 16 + 2 * t);
            dst[0] = pack_bf16(r0, r1);
            dst[4] = pack_bf16(r2, r3);
            TRACE1(8);
        }
    }
}

typedef CUresult (*EncodeTiledFn)(CUtensorMap*, CUtensorMapDataType, cuuint32_t, void*, const cuuint64_t*, const cuuint64_t*,
                                  const cuuint32_t*, const cuuint32_t*, CUtensorMapInterleave, CUtensorMapSwizzle,
                                  CUtensorMapL2promotion, CUtensorMapFloatOOBfill);

void encode_2d(EncodeTiledFn fn, CUtensorMap* map, void* base, uint64_t cols, uint64_t rows, uint32_t box_rows) {
    const cuuint64_t dims[2] = {cols, rows};
    const cuuint64_t strides[1] = {cols * 2};
    const cuuint32_t box[2] = {64, box_rows};
    const cuuint32_t elem[2] = {1, 1};
    fn(map, CU_TENSOR_MAP_DATA_TYPE_BFLOAT16, 2, base, dims, strides, box, elem, CU_TENSOR_MAP_INTERLEAVE_NONE,
       CU_TENSOR_MAP_SWIZZLE_128B, CU_TENSOR_MAP_L2_PROMOTION_L2_256B, CU_TENSOR_MAP_FLOAT_OOB_FILL_NONE);
}

void encode_kv(EncodeTiledFn fn, CUtensorMap* map, void* base) {
    const cuuint64_t dims[4] = {64, 8, 2, 65536};
    const cuuint64_t strides[3] = {256, 128, 2048};
    const cuuint32_t box[4] = {64, 8, 2, 8};
    const cuuint32_t elem[4] = {1, 1, 1, 1};
    fn(map, CU_TENSOR_MAP_DATA_TYPE_BFLOAT16, 4, base, dims, strides, box, elem, CU_TENSOR_MAP_INTERLEAVE_NONE,
       CU_TENSOR_MAP_SWIZZLE_128B, CU_TENSOR_MAP_L2_PROMOTION_L2_256B, CU_TENSOR_MAP_FLOAT_OOB_FILL_NONE);
}

}

extern "C" void kernel_launch(void* const* d_in, const int* in_sizes, int n_in, void* d_out, int out_size) {
    (void)in_sizes; (void)n_in; (void)out_size;
    static EncodeTiledFn encode = nullptr;
    static Scratch* scratch = nullptr;
    if (!encode) {
        cudaGetSymbolAddress((void**)&scratch, g_scratch);
        void* fn = nullptr;
        cudaDriverEntryPointQueryResult status;
        cudaGetDriverEntryPoint("cuTensorMapEncodeTiled", &fn, cudaEnableDefault, &status);
        encode = (EncodeTiledFn)fn;
        cudaFuncSetAttribute(gqa_block_kernel, cudaFuncAttributeMaxDynamicSharedMemorySize, kSmemBytes);
    }
    CUtensorMap map_k, map_v, map_wo;
    encode_kv(encode, &map_k, d_in[1]);
    encode_kv(encode, &map_v, d_in[2]);
    encode_2d(encode, &map_wo, d_in[4], 512, 4096, 128);
    gqa_block_kernel<<<kCtas, kThreads, kSmemBytes>>>((const char*)d_in[0], (const char*)d_in[3], (const char*)d_in[1], scratch,
                                                      (__nv_bfloat16*)d_out, map_k, map_v, map_wo);
}
```

```cpp
#include <cuda_runtime.h>
#include <cuda_bf16.h>
#include <cuda.h>
#include <stdint.h>

namespace {

constexpr int kCtas = 128;
constexpr int kThreads = 384;
constexpr int kInitThreads = 352;
constexpr int kSlots = 14;
constexpr int kSlotBytes = 16384;
constexpr int kPairs = 32;
constexpr int kHeadSlot = 6;
constexpr int kWoPos = 4 * kPairs;
constexpr int kItems = kWoPos + 4;
constexpr int kSmemBytes = kSlots * kSlotBytes + 512 + 2048;
constexpr int kPollLimit = 1 << 16;
constexpr long long kWaitClocks = 1ll << 25;
#define D_X0 3
#define D_MAIN 3
#define D_MIN 2
#define D_MAX 4
#define D_TAIL 3
#define TAIL_START 124
#define GAIN 128
#define PACE_STEP 2
#define QUAD 1
#define EARLY 1
#define D_PRE 3
#define PRE_END 6
#define D_CATCH 0
#define ARM_AT 8
constexpr int kDepthHead = D_X0, kDepthMain = D_MAIN, kDepthMin = D_MIN, kDepthMax = D_MAX, kDepthTail = D_TAIL;
constexpr int kTailStart = TAIL_START;
constexpr int kPaceStep = PACE_STEP;
constexpr int kPaceGain = GAIN;
constexpr int kArmAt = ARM_AT;

struct Scratch {
    uint4 qx[kCtas * 1024];
    uint4 ox[kCtas * 512];
    uint4 px[kCtas * 1024];
    unsigned flag[kCtas * 32];
    unsigned epoch[kCtas * 32];
    unsigned progress[2 * 32];
};
__device__ Scratch g_scratch;
#define TRACE(i)
#define TRACE1(i)
#define LAND(i)

__device__ __forceinline__ uint32_t smem_u32(const void* p) { return (uint32_t)__cvta_generic_to_shared(p); }

__device__ __forceinline__ bool elect_one() {
    uint32_t p;
    asm volatile("{\n.reg .pred q;\nelect.sync _|q, 0xffffffff;\nselp.u32 %0, 1, 0, q;\n}" : "=r"(p));
    return p != 0;
}
__device__ __forceinline__ void mbar_init(uint32_t bar, int count) {
    asm volatile("mbarrier.init.shared::cta.b64 [%0], %1;" :: "r"(bar), "r"(count) : "memory");
}
__device__ __forceinline__ void mbar_expect_tx(uint32_t bar, int bytes) {
    asm volatile("mbarrier.arrive.expect_tx.shared::cta.b64 _, [%0], %1;" :: "r"(bar), "r"(bytes) : "memory");
}
__device__ __forceinline__ void mbar_arrive(uint32_t bar) {
    asm volatile("mbarrier.arrive.shared::cta.b64 _, [%0];" :: "r"(bar) : "memory");
}
__device__ __forceinline__ bool mbar_try(uint32_t bar, uint32_t parity) {
    uint32_t ok;
    asm volatile("{\n.reg .pred p;\nmbarrier.try_wait.parity.shared::cta.b64 p, [%1], %2;\nselp.u32 %0, 1, 0, p;\n}"
                 : "=r"(ok) : "r"(bar), "r"(parity) : "memory");
    return ok != 0;
}
__device__ __forceinline__ bool mbar_test(uint32_t bar, uint32_t parity) {
    uint32_t ok;
    asm volatile("{\n.reg .pred p;\nmbarrier.test_wait.parity.shared::cta.b64 p, [%1], %2;\nselp.u32 %0, 1, 0, p;\n}"
                 : "=r"(ok) : "r"(bar), "r"(parity) : "memory");
    return ok != 0;
}
__device__ __forceinline__ void mbar_wait(uint32_t bar, uint32_t parity) {
    if (mbar_try(bar, parity)) return;
    const long long t0 = clock64();
    while (!mbar_try(bar, parity))
        if (clock64() - t0 > kWaitClocks) break;
}

__device__ __forceinline__ void tma_2d(uint32_t dst, const CUtensorMap* map, int c0, int c1, uint32_t bar) {
    asm volatile("cp.async.bulk.tensor.2d.shared::cluster.global.mbarrier::complete_tx::bytes [%0], [%1, {%3, %4}], [%2];"
                 :: "r"(dst), "l"(map), "r"(bar), "r"(c0), "r"(c1) : "memory");
}
__device__ __forceinline__ void tma_kv(uint32_t dst, const CUtensorMap* map, int row_group, uint32_t bar, uint64_t policy) {
    asm volatile("cp.async.bulk.tensor.4d.shared::cluster.global.mbarrier::complete_tx::bytes.L2::cache_hint [%0], [%1, {%3, %3, %3, %4}], [%2], %5;"
                 :: "r"(dst), "l"(map), "r"(bar), "r"(0), "r"(row_group), "l"(policy) : "memory");
}
__device__ __forceinline__ void cp_async16(uint32_t dst, const void* src) {
    asm volatile("cp.async.cg.shared.global [%0], [%1], 16;" :: "r"(dst), "l"(src) : "memory");
}
__device__ __forceinline__ void map_prefetch(const CUtensorMap* map) {
    asm volatile("prefetch.tensormap [%0];" :: "l"(map) : "memory");
}

__device__ __forceinline__ uint4 ld_gpu(const uint4* p) {
    unsigned long long a, b;
    asm volatile("ld.relaxed.gpu.global.v2.b64 {%0, %1}, [%2];" : "=l"(a), "=l"(b) : "l"(p) : "memory");
    return make_uint4((uint32_t)a, (uint32_t)(a >> 32), (uint32_t)b, (uint32_t)(b >> 32));
}
__device__ __forceinline__ void st_gpu(uint4* p, uint32_t x, uint32_t y, uint32_t z, uint32_t w) {
    const unsigned long long a = (unsigned long long)x | ((unsigned long long)y << 32);
    const unsigned long long b = (unsigned long long)z | ((unsigned long long)w << 32);
    asm volatile("st.relaxed.gpu.global.v2.b64 [%0], {%1, %2};" :: "l"(p), "l"(a), "l"(b) : "memory");
}
__device__ __forceinline__ uint32_t ld_probe(const uint4* p, int word) {
    uint32_t v;
    asm volatile("ld.relaxed.gpu.global.u32 %0, [%1];" : "=r"(v) : "l"(reinterpret_cast<const uint32_t*>(p) + word) : "memory");
    return v;
}
__device__ __forceinline__ void sts128(uint32_t addr, uint32_t x, uint32_t y, uint32_t z, uint32_t w) {
    asm volatile("st.shared.v4.u32 [%0], {%1, %2, %3, %4};" :: "r"(addr), "r"(x), "r"(y), "r"(z), "r"(w) : "memory");
}
__device__ __forceinline__ uint4 lds128(uint32_t addr) {
    uint4 v;
    asm volatile("ld.shared.v4.u32 {%0, %1, %2, %3}, [%4];" : "=r"(v.x), "=r"(v.y), "=r"(v.z), "=r"(v.w) : "r"(addr) : "memory");
    return v;
}
__device__ __forceinline__ uint32_t nonzero(uint32_t w) { return w == 0u ? 0x80000000u : w; }

__device__ __forceinline__ uint32_t pack_bf16(float lo, float hi) {
    uint32_t r;
    asm("cvt.rn.bf16x2.f32 %0, %1, %2;" : "=r"(r) : "f"(hi), "f"(lo));
    return r;
}
__device__ __forceinline__ float ex2(float x) {
    float y;
    asm("ex2.approx.ftz.f32 %0, %1;" : "=f"(y) : "f"(x));
    return y;
}

__device__ __forceinline__ uint64_t make_desc(uint32_t addr, uint32_t lbo_bytes, uint32_t sbo_bytes) {
    return (uint64_t)((addr & 0x3FFFF) >> 4) | ((uint64_t)(lbo_bytes >> 4) << 16) | ((uint64_t)(sbo_bytes >> 4) << 32) | (1ull << 62);
}

__device__ __forceinline__ void wg_fence() { asm volatile("wgmma.fence.sync.aligned;" ::: "memory"); }
__device__ __forceinline__ void wg_commit() { asm volatile("wgmma.commit_group.sync.aligned;" ::: "memory"); }
template <int N> __device__ __forceinline__ void wg_wait() { asm volatile("wgmma.wait_group.sync.aligned %0;" :: "n"(N) : "memory"); }
template <int N> __device__ __forceinline__ void reg_fence(float (&r)[N]) {
#pragma unroll
    for (int i = 0; i < N; i++) asm volatile("" : "+f"(r[i]) :: "memory");
}

#define ACC8(d, o) "+f"(d[o]), "+f"(d[o + 1]), "+f"(d[o + 2]), "+f"(d[o + 3]), "+f"(d[o + 4]), "+f"(d[o + 5]), "+f"(d[o + 6]), "+f"(d[o + 7])
#define ACC32(d, o) ACC8(d, o), ACC8(d, o + 8), ACC8(d, o + 16), ACC8(d, o + 24)
#define REGS32 "{%0, %1, %2, %3, %4, %5, %6, %7, %8, %9, %10, %11, %12, %13, %14, %15, " \
               "%16, %17, %18, %19, %20, %21, %22, %23, %24, %25, %26, %27, %28, %29, %30, %31}"
#define REGS64 "{%0, %1, %2, %3, %4, %5, %6, %7, %8, %9, %10, %11, %12, %13, %14, %15, " \
               "%16, %17, %18, %19, %20, %21, %22, %23, %24, %25, %26, %27, %28, %29, %30, %31, " \
               "%32, %33, %34, %35, %36, %37, %38, %39, %40, %41, %42, %43, %44, %45, %46, %47, " \
               "%48, %49, %50, %51, %52, %53, %54, %55, %56, %57, %58, %59, %60, %61, %62, %63}"

__device__ __forceinline__ void mma_n64_ss_bt(float (&d)[32], uint64_t da, uint64_t db, int accumulate) {
    asm volatile("{\n.reg .pred p;\nsetp.ne.b32 p, %34, 0;\n"
                 "wgmma.mma_async.sync.aligned.m64n64k16.f32.bf16.bf16 " REGS32 ", %32, %33, p, 1, 1, 0, 1;\n}"
                 : ACC32(d, 0) : "l"(da), "l"(db), "r"(accumulate));
}
template <int TB>
__device__ __forceinline__ void mma_n64_rs(float (&d)[32], const uint32_t* a, uint64_t db, int accumulate) {
    asm volatile("{\n.reg .pred p;\nsetp.ne.b32 p, %37, 0;\n"
                 "wgmma.mma_async.sync.aligned.m64n64k16.f32.bf16.bf16 " REGS32 ", {%32, %33, %34, %35}, %36, p, 1, 1, %38;\n}"
                 : ACC32(d, 0) : "r"(a[0]), "r"(a[1]), "r"(a[2]), "r"(a[3]), "l"(db), "r"(accumulate), "n"(TB));
}
__device__ __forceinline__ void mma_n128_rs_bt(float (&d)[64], const uint32_t* a, uint64_t db) {
    asm volatile("{\n.reg .pred p;\nsetp.ne.b32 p, 1, 0;\n"
                 "wgmma.mma_async.sync.aligned.m64n128k16.f32.bf16.bf16 " REGS64 ", {%64, %65, %66, %67}, %68, p, 1, 1, 1;\n}"
                 : ACC32(d, 0), ACC32(d, 32) : "r"(a[0]), "r"(a[1]), "r"(a[2]), "r"(a[3]), "l"(db));
}

__device__ __forceinline__ int pos_k(int p) { return 8 * (p >> 1) + 2 * (p & 1); }
__device__ __forceinline__ int pos_v(int p) { return pos_k(p) + 4; }
__device__ __forceinline__ bool item_is_v(int pos) { return pos & 4; }
__device__ __forceinline__ int item_tile(int pos) { return (pos >> 3) * 4 + (pos & 3); }

template <int V> struct Const { static constexpr int value = V; };
template <int N, int I = 0, typename F> __device__ __forceinline__ void static_for(F&& f) {
    if constexpr (I < N) { f(Const<I>{}); static_for<N, I + 1>(f); }
}

__device__ __forceinline__ unsigned launch_tag(const Scratch* sc, int cta) {
    return (*(const volatile unsigned*)&sc->epoch[cta * 32] + 1u) | 0x80000000u;
}

struct Ring {
    uint32_t base, full, empty;
    __device__ __forceinline__ uint32_t wait(int pos) const {
        const int slot = pos % kSlots;
        mbar_wait(full + 8 * slot, (pos / kSlots) & 1);
        return base + slot * kSlotBytes;
    }
    __device__ __forceinline__ void release(int pos, int lane) const {
        if (lane == 0) mbar_arrive(empty + 8 * (pos % kSlots));
    }
};

__global__ void __launch_bounds__(kThreads, 1)
gqa_block_kernel(const char* __restrict__ x_raw, const char* __restrict__ wq_raw, Scratch* __restrict__ sc,
                 __nv_bfloat16* __restrict__ out, const __grid_constant__ CUtensorMap map_k,
                 const __grid_constant__ CUtensorMap map_v, const __grid_constant__ CUtensorMap map_wo) {
    extern __shared__ __align__(1024) char smem_raw[];
    const int cta = blockIdx.x;
    const int warp = __shfl_sync(0xffffffffu, threadIdx.x >> 5, 0), lane = threadIdx.x & 31;
    const int b = cta >> 3, h = cta & 7;
    const int bg = b >> 3, j = b & 7;

    Ring ring;
    ring.base = smem_u32(smem_raw);
    ring.full = ring.base + kSlots * kSlotBytes;
    ring.empty = ring.full + 8 * kSlots;
    const uint32_t peers_ready = ring.empty + 8 * kSlots;
    const uint32_t q_ready = peers_ready + 8;
    const uint32_t pace = q_ready + 8;
    const uint32_t stats = ring.full + 512;

    uint64_t stream_policy;
    asm volatile("createpolicy.fractional.L2::evict_first.b64 %0, 1.0;" : "=l"(stream_policy));
    if (warp == 8) {
        if (elect_one()) {
#pragma unroll
            for (int i = 0; i < EARLY; i++) mbar_init(ring.full + 8 * i, 1);
            asm volatile("fence.mbarrier_init.release.cluster;" ::: "memory");
#pragma unroll
            for (int i = 0; i < EARLY; i++) {
                mbar_expect_tx(ring.full + 8 * i, kSlotBytes);
                tma_kv(ring.base + i * kSlotBytes, &map_k, cta * 512 + i * 8, ring.full + 8 * i, stream_policy);
            }
            map_prefetch(&map_v);
#pragma unroll
            for (int i = EARLY; i < kSlots; i++) mbar_init(ring.full + 8 * i, 1);
#pragma unroll
            for (int i = 0; i < kSlots; i++) mbar_init(ring.empty + 8 * i, 4);
            mbar_init(peers_ready, 1);
            mbar_init(q_ready, 4);
            asm volatile("st.volatile.shared.v2.u32 [%0], {%1, %2};" :: "r"(pace), "r"(kDepthMain), "r"(0) : "memory");
            asm volatile("fence.mbarrier_init.release.cluster;" ::: "memory");
        }
        __syncwarp();
        asm volatile("bar.arrive 1, %0;" :: "n"(kInitThreads) : "memory");
    }

    if (warp >= 8) {
        asm volatile("setmaxnreg.dec.sync.aligned.u32 40;");
        if (warp == 8) {
            if (elect_one()) {
                int slot = EARLY, lap = 0;
                bool started = false;
                for (int pos = EARLY; pos < kItems; pos++) {
                    const int releases = lap + (slot >= kHeadSlot);
                    if (releases > 0) mbar_wait(ring.empty + 8 * slot, (releases - 1) & 1);
                    if (!started) started = mbar_test(q_ready, 0);
                    int depth;
                    asm volatile("st.volatile.shared.u32 [%0], %1;" :: "r"(pace + 4), "r"(pos) : "memory");
                    asm volatile("ld.volatile.shared.u32 %0, [%1];" : "=r"(depth) : "r"(pace) : "memory");
                    if (!started) depth = pos < PRE_END ? D_PRE : kDepthHead;
                    else if (D_CATCH && pos < 24) depth = D_CATCH;
                    if (pos >= kTailStart) depth = pos < kWoPos ? kDepthTail : 1;
                    if (pos >= depth) ring.wait(pos - depth);
                    const uint32_t bar = ring.full + 8 * slot, dst = ring.base + slot * kSlotBytes;
                    mbar_expect_tx(bar, kSlotBytes);
                    if (pos < kWoPos) {
                        tma_kv(dst, item_is_v(pos) ? &map_v : &map_k, cta * 512 + item_tile(pos) * 8, bar, stream_policy);
                        if (pos == 100) map_prefetch(&map_wo);
                    } else {
                        tma_2d(dst, &map_wo, j * 64, h * 512 + (pos - kWoPos) * 128, bar);
                    }
                    if (++slot == kSlots) { slot = 0; lap++; }
                }
            }
        } else if (warp == 9) {
            const unsigned epoch = launch_tag(sc, cta);
            const int peer = (lane & 8) ? b * 8 + (lane & 7) : (bg * 8 + (lane & 7)) * 8 + h;
            asm volatile("bar.sync 1, %0;" :: "n"(kInitThreads) : "memory");
            asm volatile("bar.sync 3, 288;" ::: "memory");
            if (lane == 0) {
                asm volatile("fence.acq_rel.gpu;" ::: "memory");
                asm volatile("st.relaxed.gpu.global.u32 [%0], %1;" :: "l"(&sc->flag[cta * 32]), "r"(epoch) : "memory");
                sc->epoch[cta * 32] = epoch;
                if (cta == 0) sc->progress[((epoch & 1) ^ 1) * 32] = 0;
            }
            __syncwarp();
            unsigned v;
            int it = 0;
            do {
                __nanosleep(500);
                asm volatile("ld.acquire.gpu.global.u32 %0, [%1];" : "=r"(v) : "l"(&sc->flag[peer * 32]) : "memory");
            } while (v != epoch && ++it < kPollLimit);
            __syncwarp();
            if (lane == 0) mbar_arrive(peers_ready);
        } else if (warp == 10) {
            const unsigned epoch = launch_tag(sc, cta);
            asm volatile("bar.sync 1, %0;" :: "n"(kInitThreads) : "memory");
            if (lane == 0) {
                int done = 0;
                for (int it = 0; done < kTailStart / kPaceStep && it < kPollLimit; it++) {
                    int pos;
                    asm volatile("ld.volatile.shared.u32 %0, [%1];" : "=r"(pos) : "r"(pace + 4) : "memory");
                    const int now = pos / kPaceStep;
                    if (now > done) {
                        unsigned seen;
                        asm volatile("atom.relaxed.gpu.global.add.u32 %0, [%1], %2;" : "=r"(seen)
                                     : "l"(&sc->progress[(epoch & 1) * 32]), "r"(now - done) : "memory");
                        const int lag = ((int)seen - kCtas / 2 - kCtas * (now - 1)) * kPaceStep;
                        const int depth = kDepthMain + (lag + kPaceGain / 2 + 64 * kPaceGain) / kPaceGain - 64;
                        if (now > 2)
                            asm volatile("st.volatile.shared.u32 [%0], %1;" :: "r"(pace), "r"(min(max(depth, kDepthMin), kDepthMax)) : "memory");
                        done = now;
                    } else {
                        __nanosleep(100);
                    }
                }
            }
        }
    } else {
        TRACE(0);
        const int wg = warp >> 2, wq = warp & 3;
        const int g = lane >> 2, t = lane & 3;
        const bool active = (wq >> 1) == wg;
        const int hp = wq & 1;

        {
            const int tid = threadIdx.x;
            const int xr = tid >> 4, xc = tid & 15, wr = tid >> 3, wc = tid & 7;
            const char* xs = x_raw + (size_t)(bg * 64 + xr) * 1024 + xc * 16;
            const char* ws = wq_raw + (size_t)wr * 8192 + (h * 512 + j * 64) * 2 + wc * 16;
            const uint32_t xd = ring.base + kHeadSlot * kSlotBytes + (xc >> 3) * 8192 + xr * 128 + (((xc ^ xr) & 7) << 4);
            const uint32_t wd = ring.base + (kHeadSlot + 1) * kSlotBytes + wr * 128 + (((wc ^ wr) & 7) << 4);
#pragma unroll
            for (int c = 0; c < 4; c++) {
#pragma unroll
                for (int i = 0; i < 4; i++) {
                    cp_async16(wd + c * 2 * kSlotBytes + i * 4096, ws + (size_t)(c * 128 + i * 32) * 8192);
                    cp_async16(xd + c * 2 * kSlotBytes + i * 2048, xs + i * 16384 + c * 256);
                }
                asm volatile("cp.async.commit_group;" ::: "memory");
            }
        }
        const unsigned epoch = launch_tag(sc, cta);
        uint4* const qx_dst = sc->qx + (((bg * 8 + 2 * wq) * 8 + h) * 8 + j) * 128 + lane;
        uint4* const ox_mine = sc->ox + cta * 512 + hp * 256 + lane;
        uint4* const px_dst = sc->px + ((b * 8 + 2 * wq) * 8 + h) * 128 + lane;
        asm volatile("setmaxnreg.inc.sync.aligned.u32 232;");
        asm volatile("bar.sync 1, %0;" :: "n"(kInitThreads) : "memory");

        float s[32];
        auto chunk_landed = [&](auto c) {
            asm volatile("cp.async.wait_group %0;" :: "n"(3 - c.value) : "memory");
            asm volatile("fence.proxy.async.shared::cta;" ::: "memory");
        };
        if (wg == 0) {
            static_for<4>([&](auto c) {
                chunk_landed(c);
                asm volatile("bar.sync %0, 256;" :: "n"(5 + c.value) : "memory");
                LAND(c.value);
                const uint32_t xa = ring.base + (kHeadSlot + 2 * c.value) * kSlotBytes, wa = xa + kSlotBytes;
                wg_fence();
#pragma unroll
                for (int ks = 0; ks < 8; ks++)
                    mma_n64_ss_bt(s, make_desc(xa + (ks >> 2) * 8192 + (ks & 3) * 32, 16, 1024),
                                  make_desc(wa + ks * 2048, 16, 1024), c.value | ks);
                wg_commit();
                wg_wait<0>();
                ring.release(kHeadSlot + 2 * c.value, lane);
                ring.release(kHeadSlot + 2 * c.value + 1, lane);
            });
            reg_fence(s);
            TRACE(1);
#pragma unroll
            for (int r = 0; r < 2; r++)
#pragma unroll
                for (int c = 0; c < 4; c++) {
                    const float* a = s + 8 * c + 2 * r;
                    st_gpu(qx_dst + r * 8192 + c * 32, pack_bf16(a[0], a[1]), epoch, pack_bf16(a[4], a[5]), epoch);
                }
            asm volatile("bar.arrive 9, 256;" ::: "memory");
        } else {
            static_for<4>([&](auto c) {
                chunk_landed(c);
                asm volatile("bar.arrive %0, 256;" :: "n"(5 + c.value) : "memory");
            });
            asm volatile("bar.sync 9, 256;" ::: "memory");
        }

        uint32_t qa[32];
#pragma unroll
        for (int i = 0; i < 32; i++) qa[i] = 0;
        if (active) {
            const uint4* src = sc->qx + (cta * 8 + 4 * hp) * 128 + lane;
            int it = 0;
            const uint4* probe = sc->qx + (cta * 8 + 4 * hp + (lane & 3)) * 128 + 127;
            while (!__all_sync(0xffffffffu, lane >= 4 || ld_probe(probe, 3) == epoch))
                if (++it > kPollLimit) break;
            TRACE(9);
            while (true) {
                uint32_t stale = 0;
#pragma unroll
                for (int r = 0; r < 2; r++)
#pragma unroll
                    for (int c = 0; c < 8; c++) {
                        const uint4 v = ld_gpu(src + (r * 8 + c) * 32);
                        qa[4 * c + r] = v.x; qa[4 * c + 2 + r] = v.z;
                        stale |= (v.y ^ epoch) | (v.w ^ epoch);
                    }
                if (__all_sync(0xffffffffu, stale == 0)) break;
                if (++it > kPollLimit) break;
            }
            if (lane == 0) mbar_arrive(q_ready);
        }
        TRACE(2);

        const float kScale = 0.08838834764831845f * 1.4426950408889634f;
        float o[64];
#pragma unroll
        for (int i = 0; i < 64; i++) o[i] = 0.f;
        uint32_t pa[16];
#pragma unroll
        for (int i = 0; i < 16; i++) pa[i] = 0;
        float m0 = -INFINITY, m1 = -INFINITY, l0 = 0.f, l1 = 0.f;

        auto issue_qk = [&](int pos, float (&s)[32]) {
            const uint32_t ka = ring.wait(pos);
            wg_fence();
#pragma unroll
            for (int ks = 0; ks < 8; ks++)
                mma_n64_rs<0>(s, qa + 4 * ks, make_desc(ka + (ks >> 2) * 1024 + (ks & 3) * 32, 16, 2048), ks);
            wg_commit();
        };
        auto issue_pv = [&](int pos, const uint32_t (&pf)[16]) {
            const uint32_t va = ring.wait(pos);
            wg_fence();
#pragma unroll
            for (int ks = 0; ks < 4; ks++) mma_n128_rs_bt(o, pf + 4 * ks, make_desc(va + ks * 4096, 1024, 2048));
            wg_commit();
        };
        float alpha0 = 1.f, alpha1 = 1.f;
        auto softmax = [&](float (&s)[32]) {
            float x0 = fmaxf(s[0], s[1]), x1 = fmaxf(s[2], s[3]);
#pragma unroll
            for (int i = 1; i < 8; i++) {
                x0 = fmaxf(x0, fmaxf(s[4 * i], s[4 * i + 1]));
                x1 = fmaxf(x1, fmaxf(s[4 * i + 2], s[4 * i + 3]));
            }
            x0 = fmaxf(x0, __shfl_xor_sync(0xffffffffu, x0, 1));
            x1 = fmaxf(x1, __shfl_xor_sync(0xffffffffu, x1, 1));
            x0 = fmaxf(x0, __shfl_xor_sync(0xffffffffu, x0, 2));
            x1 = fmaxf(x1, __shfl_xor_sync(0xffffffffu, x1, 2));
            const float n0 = fmaxf(m0, x0), n1 = fmaxf(m1, x1);
            alpha0 = ex2((m0 - n0) * kScale);
            alpha1 = ex2((m1 - n1) * kScale);
            m0 = n0; m1 = n1;
            const float b0 = -n0 * kScale, b1 = -n1 * kScale;
            float r0 = 0.f, r1 = 0.f;
#pragma unroll
            for (int i = 0; i < 8; i++) {
                s[4 * i] = ex2(fmaf(s[4 * i], kScale, b0));
                s[4 * i + 1] = ex2(fmaf(s[4 * i + 1], kScale, b0));
                s[4 * i + 2] = ex2(fmaf(s[4 * i + 2], kScale, b1));
                s[4 * i + 3] = ex2(fmaf(s[4 * i + 3], kScale, b1));
                r0 += s[4 * i] + s[4 * i + 1];
                r1 += s[4 * i + 2] + s[4 * i + 3];
            }
            l0 = fmaf(l0, alpha0, r0);
            l1 = fmaf(l1, alpha1, r1);
        };
        auto rescale_and_pack = [&]() {
#pragma unroll
            for (int i = 0; i < 16; i++) {
                o[4 * i] *= alpha0; o[4 * i + 1] *= alpha0;
                o[4 * i + 2] *= alpha1; o[4 * i + 3] *= alpha1;
                pa[i] = pack_bf16(s[2 * i], s[2 * i + 1]);
            }
        };

        {
            const int pos = wg;
            issue_qk(pos, s);
            wg_wait<0>();
            reg_fence(s);
            ring.release(pos, lane);
            if (active) { softmax(s); rescale_and_pack(); }
        }
        TRACE(3);
        int vpos = pos_v(0) + wg;
#pragma unroll 1
        for (int p = 1; p < kPairs - 1; p++) {
            const int kpos = pos_k(p) + wg;
            issue_qk(kpos, s);
            issue_pv(vpos, pa);
            wg_wait<1>();
            reg_fence(s);
            ring.release(kpos, lane);
            if (active) softmax(s);
            wg_wait<0>();
            reg_fence(o);
            ring.release(vpos, lane);
            if (active) rescale_and_pack();
            vpos = pos_v(p) + wg;
            if (p == kArmAt) {
                if (wg == 0) {
#pragma unroll
                    for (int c = 0; c < 8; c++) st_gpu(px_dst + (c >> 2) * 1024 + (c & 3) * 32, 0, 0, 0, 0);
                } else if (active) {
#pragma unroll
                    for (int c = 0; c < 8; c++) st_gpu(ox_mine + c * 32, 0, 0, 0, 0);
                }
                asm volatile("bar.arrive 3, 288;" ::: "memory");
            }
        }
        mbar_wait(peers_ready, 0);

        const uint32_t part = ring.base + (pos_k(kPairs - 1) % kSlots) * kSlotBytes + hp * 8192 + lane * 16;
        const uint32_t part_p = ring.base + (pos_k(kPairs - 2) % kSlots) * kSlotBytes + hp * 2048 + lane * 16;
        float s2[32];
        uint32_t pb[16];
#pragma unroll
        for (int i = 0; i < 16; i++) pb[i] = 0;
        issue_qk(pos_k(kPairs - 1) + wg, s2);
        wg_wait<0>();
        reg_fence(s2);
        if (active) {
            softmax(s2);
            l0 += __shfl_xor_sync(0xffffffffu, l0, 1);
            l1 += __shfl_xor_sync(0xffffffffu, l1, 1);
            l0 += __shfl_xor_sync(0xffffffffu, l0, 2);
            l1 += __shfl_xor_sync(0xffffffffu, l1, 2);
            sts128(stats + ((wg * 2 + hp) * 32 + lane) * 16, __float_as_uint(m0), __float_as_uint(m1), __float_as_uint(l0), __float_as_uint(l1));
            asm volatile("bar.sync 10, 128;" ::: "memory");
            const uint4 st = lds128(stats + (((wg ^ 1) * 2 + hp) * 32 + lane) * 16);
            const float pm0 = __uint_as_float(st.x), pm1 = __uint_as_float(st.y);
            const float n0 = fmaxf(m0, pm0), n1 = fmaxf(m1, pm1);
            float f0 = ex2((m0 - n0) * kScale), f1 = ex2((m1 - n1) * kScale);
            f0 /= l0 * f0 + __uint_as_float(st.z) * ex2((pm0 - n0) * kScale);
            f1 /= l1 * f1 + __uint_as_float(st.w) * ex2((pm1 - n1) * kScale);
            alpha0 *= f0;
            alpha1 *= f1;
#pragma unroll
            for (int i = 0; i < 8; i++) {
                pb[2 * i] = pack_bf16(s2[4 * i] * f0, s2[4 * i + 1] * f0);
                pb[2 * i + 1] = pack_bf16(s2[4 * i + 2] * f1, s2[4 * i + 3] * f1);
                s[4 * i] *= alpha0; s[4 * i + 1] *= alpha0;
                s[4 * i + 2] *= alpha1; s[4 * i + 3] *= alpha1;
            }
            rescale_and_pack();
        }

        if (wg == 0) {
            if (active) {
#pragma unroll
                for (int c = 0; c < 4; c++) sts128(part_p + c * 512, pb[4 * c], pb[4 * c + 1], pb[4 * c + 2], pb[4 * c + 3]);
                asm volatile("bar.arrive 12, 128;" ::: "memory");
            }
            issue_pv(vpos, pa);
            wg_wait<0>();
            reg_fence(o);
            if (active) {
#pragma unroll
                for (int c = 0; c < 16; c++)
                    sts128(part + c * 512, __float_as_uint(o[4 * c]), __float_as_uint(o[4 * c + 1]),
                           __float_as_uint(o[4 * c + 2]), __float_as_uint(o[4 * c + 3]));
                asm volatile("bar.arrive 4, 128;" ::: "memory");
            }
            TRACE(4);

            uint32_t oa[128];
#pragma unroll
            for (int i = 0; i < 128; i++) oa[i] = 0;
            {
                const uint4* src = sc->ox + ((bg * 8 + 2 * wq) * 8 + h) * 512 + lane;
                const uint4* probe = sc->ox + ((bg * 8 + 2 * wq + ((lane >> 1) & 1)) * 8 + h) * 512 + (lane & 1) * 256 + 255;
                uint32_t pending = 3;
                int it = 0;
                while (true) {
                    uint32_t seen = __ballot_sync(0xffffffffu, lane < 4 && ld_probe(probe, 2) != 0);
                    seen = ((seen & 3) == 3) | ((seen >> 2) == 3) << 1;
#pragma unroll
                    for (int r = 0; r < 2; r++) {
                        if ((pending & seen) >> r & 1) {
                            uint32_t low = 0xffffffffu;
#pragma unroll
                            for (int c = 0; c < 16; c++) {
                                const uint4 v = ld_gpu(src + r * 8 * 512 + c * 32);
                                oa[8 * c + r] = v.x; oa[8 * c + 2 + r] = v.y; oa[8 * c + 4 + r] = v.z; oa[8 * c + 6 + r] = v.w;
                            }
#pragma unroll
                            for (int c = 0; c < 16; c++) low = __vimin3_u32(low, oa[8 * c + r], oa[8 * c + 4 + r]);
                            if (__all_sync(0xffffffffu, low != 0)) pending &= ~(1u << r);
                        }
                    }
                    if (pending == 0) break;
                    if (++it > kPollLimit) break;
                }
            }
            TRACE(6);

#pragma unroll
            for (int c = 0; c < 4; c++) {
                const uint32_t wa = ring.wait(kWoPos + c);
                wg_fence();
#pragma unroll
                for (int ks = 0; ks < 8; ks++)
                    mma_n64_rs<1>(s, oa + 32 * c + 4 * ks, make_desc(wa + ks * 2048, 16, 1024), c | ks);
                wg_commit();
            }
            wg_wait<0>();
            reg_fence(s);
            TRACE(7);
#pragma unroll
            for (int r = 0; r < 2; r++)
#pragma unroll
                for (int c = 0; c < 4; c++) {
                    const float* a = s + 8 * c + 2 * r;
                    st_gpu(px_dst + r * 1024 + c * 32, nonzero(__float_as_uint(a[0])), __float_as_uint(a[1]),
                           nonzero(__float_as_uint(a[4])), __float_as_uint(a[5]));
                }
        } else {
            uint32_t pc[16];
#pragma unroll
            for (int i = 0; i < 16; i++) pc[i] = 0;
            if (active) {
                asm volatile("bar.sync 12, 128;" ::: "memory");
#pragma unroll
                for (int c = 0; c < 4; c++) {
                    const uint4 v = lds128(part_p + c * 512);
                    pc[4 * c] = v.x; pc[4 * c + 1] = v.y; pc[4 * c + 2] = v.z; pc[4 * c + 3] = v.w;
                }
            }
            issue_pv(vpos, pa);
            issue_pv(pos_v(kPairs - 1), pc);
            issue_pv(pos_v(kPairs - 1) + 1, pb);
            uint4 other[16];
            if (active) {
                asm volatile("bar.sync 4, 128;" ::: "memory");
#pragma unroll
                for (int c = 0; c < 16; c++) other[c] = lds128(part + c * 512);
            }
            wg_wait<0>();
            reg_fence(o);
            TRACE1(11);
            if (active) {
                uint32_t w[32];
#pragma unroll
                for (int i = 0; i < 16; i++) {
                    w[i] = pack_bf16(o[4 * i] + __uint_as_float(other[i].x), o[4 * i + 1] + __uint_as_float(other[i].y));
                    w[16 + i] = pack_bf16(o[4 * i + 2] + __uint_as_float(other[i].z), o[4 * i + 3] + __uint_as_float(other[i].w));
                }
#pragma unroll
                for (int c = 0; c < 8; c++)
                    st_gpu(ox_mine + c * 32, nonzero(w[4 * c]), w[4 * c + 1], nonzero(w[4 * c + 2]), w[4 * c + 3]);
            }
            TRACE1(5);

            const uint4* src = sc->px + cta * 1024 + wq * 32 + lane;
            uint4 v[8];
            int it = 0;
            const uint4* probe = sc->px + cta * 1024 + (lane & 7) * 128 + wq * 32 + 31;
            while (!__any_sync(0xffffffffu, lane < 8 && ld_probe(probe, 2) != 0))
                if (++it > kPollLimit) break;
#pragma unroll
            for (int i = 0; i < 8; i++) v[i] = make_uint4(0, 0, 0, 0);
            while (true) {
                uint32_t low = 0xffffffffu;
#pragma unroll
                for (int i = 0; i < 8; i++) if (v[i].x == 0 || v[i].z == 0) v[i] = ld_gpu(src + i * 128);
#pragma unroll
                for (int i = 0; i < 8; i++) low = __vimin3_u32(low, v[i].x, v[i].z);
                if (low != 0) break;
                if (++it > kPollLimit) break;
            }
            float r0 = 0.f, r1 = 0.f, r2 = 0.f, r3 = 0.f;
#pragma unroll
            for (int i = 0; i < 8; i++) {
                r0 += __uint_as_float(v[i].x); r1 += __uint_as_float(v[i].y);
                r2 += __uint_as_float(v[i].z); r3 += __uint_as_float(v[i].w);
            }
            uint32_t* dst = reinterpret_cast<uint32_t*>(out + ((bg * 8 + h) * 8 + g) * 512 + j * 64 + wq * 16 + 2 * t);
            dst[0] = pack_bf16(r0, r1);
            dst[4] = pack_bf16(r2, r3);
            TRACE1(8);
        }
    }
}

typedef CUresult (*EncodeTiledFn)(CUtensorMap*, CUtensorMapDataType, cuuint32_t, void*, const cuuint64_t*, const cuuint64_t*,
                                  const cuuint32_t*, const cuuint32_t*, CUtensorMapInterleave, CUtensorMapSwizzle,
                                  CUtensorMapL2promotion, CUtensorMapFloatOOBfill);

void encode_2d(EncodeTiledFn fn, CUtensorMap* map, void* base, uint64_t cols, uint64_t rows, uint32_t box_rows) {
    const cuuint64_t dims[2] = {cols, rows};
    const cuuint64_t strides[1] = {cols * 2};
    const cuuint32_t box[2] = {64, box_rows};
    const cuuint32_t elem[2] = {1, 1};
    fn(map, CU_TENSOR_MAP_DATA_TYPE_BFLOAT16, 2, base, dims, strides, box, elem, CU_TENSOR_MAP_INTERLEAVE_NONE,
       CU_TENSOR_MAP_SWIZZLE_128B, CU_TENSOR_MAP_L2_PROMOTION_L2_256B, CU_TENSOR_MAP_FLOAT_OOB_FILL_NONE);
}

void encode_kv(EncodeTiledFn fn, CUtensorMap* map, void* base) {
    const cuuint64_t dims[4] = {64, 8, 2, 65536};
    const cuuint64_t strides[3] = {256, 128, 2048};
    const cuuint32_t box[4] = {64, 8, 2, 8};
    const cuuint32_t elem[4] = {1, 1, 1, 1};
    fn(map, CU_TENSOR_MAP_DATA_TYPE_BFLOAT16, 4, base, dims, strides, box, elem, CU_TENSOR_MAP_INTERLEAVE_NONE,
       CU_TENSOR_MAP_SWIZZLE_128B, CU_TENSOR_MAP_L2_PROMOTION_L2_256B, CU_TENSOR_MAP_FLOAT_OOB_FILL_NONE);
}

}

extern "C" void kernel_launch(void* const* d_in, const int* in_sizes, int n_in, void* d_out, int out_size) {
    (void)in_sizes; (void)n_in; (void)out_size;
    static EncodeTiledFn encode = nullptr;
    static Scratch* scratch = nullptr;
    if (!encode) {
        cudaGetSymbolAddress((void**)&scratch, g_scratch);
        void* fn = nullptr;
        cudaDriverEntryPointQueryResult status;
        cudaGetDriverEntryPoint("cuTensorMapEncodeTiled", &fn, cudaEnableDefault, &status);
        encode = (EncodeTiledFn)fn;
        cudaFuncSetAttribute(gqa_block_kernel, cudaFuncAttributeMaxDynamicSharedMemorySize, kSmemBytes);
    }
    CUtensorMap map_k, map_v, map_wo;
    encode_kv(encode, &map_k, d_in[1]);
    encode_kv(encode, &map_v, d_in[2]);
    encode_2d(encode, &map_wo, d_in[4], 512, 4096, 128);
    gqa_block_kernel<<<kCtas, kThreads, kSmemBytes>>>((const char*)d_in[0], (const char*)d_in[3], scratch,
                                                      (__nv_bfloat16*)d_out, map_k, map_v, map_wo);
}
```

```cpp
#include <cuda_runtime.h>
#include <cuda_bf16.h>
#include <cuda.h>
#include <stdint.h>

namespace {

constexpr int kCtas = 128;
constexpr int kThreads = 384;
constexpr int kInitThreads = 352;
constexpr int kSlots = 14;
constexpr int kSlotBytes = 16384;
constexpr int kPairs = 32;
constexpr int kHeadSlot = 6;
constexpr int kWoPos = 4 * kPairs;
constexpr int kItems = kWoPos + 4;
constexpr int kSmemBytes = kSlots * kSlotBytes + 512 + 2048;
constexpr int kPollLimit = 1 << 16;
constexpr long long kWaitClocks = 1ll << 25;
#define D_X0 4
#define D_MAIN 3
#define D_MIN 2
#define D_MAX 4
#define D_TAIL 2
#define TAIL_START 124
#define GAIN 96
#define PACE_STEP 2
#define QUAD 1
#define EARLY 2
#define D_PRE 3
#define PRE_END 6
#define D_CATCH 0
#define X2_WIDE 1
#define X0_PROBE 1
#define WARM_PROBE 0
#define WO_PAT 0x2111
#define PROBE_CHUNK 0
#define BOTH 0
#define WO_EF 0
#define WO_PROMO 2
#define KV_PROMO 2
#define CPA 0
#define ARM_AT 8
constexpr int kDepthHead = D_X0, kDepthMain = D_MAIN, kDepthMin = D_MIN, kDepthMax = D_MAX, kDepthTail = D_TAIL;
constexpr int kTailStart = TAIL_START;
constexpr int kPaceStep = PACE_STEP;
constexpr int kPaceGain = GAIN;
constexpr int kArmAt = ARM_AT;

struct Scratch {
    uint4 qx[2 * kCtas * 512];
    uint4 ox[kCtas * 512];
    uint4 px[kCtas * 512];
    unsigned flag[kCtas * 32];
    unsigned epoch[kCtas * 32];
    unsigned progress[2 * 32];
};
__device__ Scratch g_scratch;
#define TRACE(i)
#define TRACE1(i)
#define LAND(i)

__device__ __forceinline__ uint32_t smem_u32(const void* p) { return (uint32_t)__cvta_generic_to_shared(p); }

__device__ __forceinline__ bool elect_one() {
    uint32_t p;
    asm volatile("{\n.reg .pred q;\nelect.sync _|q, 0xffffffff;\nselp.u32 %0, 1, 0, q;\n}" : "=r"(p));
    return p != 0;
}
__device__ __forceinline__ void mbar_init(uint32_t bar, int count) {
    asm volatile("mbarrier.init.shared::cta.b64 [%0], %1;" :: "r"(bar), "r"(count) : "memory");
}
__device__ __forceinline__ void mbar_expect_tx(uint32_t bar, int bytes) {
    asm volatile("mbarrier.arrive.expect_tx.shared::cta.b64 _, [%0], %1;" :: "r"(bar), "r"(bytes) : "memory");
}
__device__ __forceinline__ void mbar_arrive(uint32_t bar) {
    asm volatile("mbarrier.arrive.shared::cta.b64 _, [%0];" :: "r"(bar) : "memory");
}
__device__ __forceinline__ bool mbar_try(uint32_t bar, uint32_t parity) {
    uint32_t ok;
    asm volatile("{\n.reg .pred p;\nmbarrier.try_wait.parity.shared::cta.b64 p, [%1], %2;\nselp.u32 %0, 1, 0, p;\n}"
                 : "=r"(ok) : "r"(bar), "r"(parity) : "memory");
    return ok != 0;
}
__device__ __forceinline__ bool mbar_test(uint32_t bar, uint32_t parity) {
    uint32_t ok;
    asm volatile("{\n.reg .pred p;\nmbarrier.test_wait.parity.shared::cta.b64 p, [%1], %2;\nselp.u32 %0, 1, 0, p;\n}"
                 : "=r"(ok) : "r"(bar), "r"(parity) : "memory");
    return ok != 0;
}
__device__ __forceinline__ void mbar_wait(uint32_t bar, uint32_t parity) {
    if (mbar_try(bar, parity)) return;
    const long long t0 = clock64();
    while (!mbar_try(bar, parity))
        if (clock64() - t0 > kWaitClocks) break;
}

__device__ __forceinline__ void tma_2d(uint32_t dst, const CUtensorMap* map, int c0, int c1, uint32_t bar) {
    asm volatile("cp.async.bulk.tensor.2d.shared::cluster.global.mbarrier::complete_tx::bytes [%0], [%1, {%3, %4}], [%2];"
                 :: "r"(dst), "l"(map), "r"(bar), "r"(c0), "r"(c1) : "memory");
}
__device__ __forceinline__ void tma_kv(uint32_t dst, const CUtensorMap* map, int row_group, uint32_t bar, uint64_t policy) {
    asm volatile("cp.async.bulk.tensor.4d.shared::cluster.global.mbarrier::complete_tx::bytes.L2::cache_hint [%0], [%1, {%3, %3, %3, %4}], [%2], %5;"
                 :: "r"(dst), "l"(map), "r"(bar), "r"(0), "r"(row_group), "l"(policy) : "memory");
}
__device__ __forceinline__ void cp_async16(uint32_t dst, const void* src) {
    asm volatile("cp.async.cg.shared.global [%0], [%1], 16;" :: "r"(dst), "l"(src) : "memory");
}
__device__ __forceinline__ void map_prefetch(const CUtensorMap* map) {
    asm volatile("prefetch.tensormap [%0];" :: "l"(map) : "memory");
}

__device__ __forceinline__ uint4 ld_gpu(const uint4* p) {
    unsigned long long a, b;
    asm volatile("ld.relaxed.gpu.global.v2.b64 {%0, %1}, [%2];" : "=l"(a), "=l"(b) : "l"(p) : "memory");
    return make_uint4((uint32_t)a, (uint32_t)(a >> 32), (uint32_t)b, (uint32_t)(b >> 32));
}
__device__ __forceinline__ void st_gpu(uint4* p, uint32_t x, uint32_t y, uint32_t z, uint32_t w) {
    const unsigned long long a = (unsigned long long)x | ((unsigned long long)y << 32);
    const unsigned long long b = (unsigned long long)z | ((unsigned long long)w << 32);
    asm volatile("st.relaxed.gpu.global.v2.b64 [%0], {%1, %2};" :: "l"(p), "l"(a), "l"(b) : "memory");
}
__device__ __forceinline__ uint2 ld_gpu64(const uint2* p) {
    unsigned long long a;
    asm volatile("ld.relaxed.gpu.global.b64 %0, [%1];" : "=l"(a) : "l"(p) : "memory");
    return make_uint2((uint32_t)a, (uint32_t)(a >> 32));
}
__device__ __forceinline__ void st_gpu64(uint2* p, uint32_t x, uint32_t y) {
    asm volatile("st.relaxed.gpu.global.b64 [%0], %1;" :: "l"(p), "l"((unsigned long long)x | ((unsigned long long)y << 32)) : "memory");
}
__device__ __forceinline__ uint32_t ld_probe(const uint4* p, int word) {
    uint32_t v;
    asm volatile("ld.relaxed.gpu.global.u32 %0, [%1];" : "=r"(v) : "l"(reinterpret_cast<const uint32_t*>(p) + word) : "memory");
    return v;
}
__device__ __forceinline__ void sts128(uint32_t addr, uint32_t x, uint32_t y, uint32_t z, uint32_t w) {
    asm volatile("st.shared.v4.u32 [%0], {%1, %2, %3, %4};" :: "r"(addr), "r"(x), "r"(y), "r"(z), "r"(w) : "memory");
}
__device__ __forceinline__ uint4 lds128(uint32_t addr) {
    uint4 v;
    asm volatile("ld.shared.v4.u32 {%0, %1, %2, %3}, [%4];" : "=r"(v.x), "=r"(v.y), "=r"(v.z), "=r"(v.w) : "r"(addr) : "memory");
    return v;
}
__device__ __forceinline__ uint32_t nonzero(uint32_t w) { return w == 0u ? 0x80000000u : w; }

__device__ __forceinline__ uint32_t pack_bf16(float lo, float hi) {
    uint32_t r;
    asm("cvt.rn.bf16x2.f32 %0, %1, %2;" : "=r"(r) : "f"(hi), "f"(lo));
    return r;
}
__device__ __forceinline__ float ex2(float x) {
    float y;
    asm("ex2.approx.ftz.f32 %0, %1;" : "=f"(y) : "f"(x));
    return y;
}

__device__ __forceinline__ uint64_t make_desc(uint32_t addr, uint32_t lbo_bytes, uint32_t sbo_bytes) {
    return (uint64_t)((addr & 0x3FFFF) >> 4) | ((uint64_t)(lbo_bytes >> 4) << 16) | ((uint64_t)(sbo_bytes >> 4) << 32) | (1ull << 62);
}

__device__ __forceinline__ uint64_t advance(uint64_t desc, uint32_t bytes) {
    return (desc & 0xFFFFFFFF00000000ull) | (uint32_t)((uint32_t)desc + (bytes >> 4));
}

__device__ __forceinline__ void wg_fence() { asm volatile("wgmma.fence.sync.aligned;" ::: "memory"); }
__device__ __forceinline__ void wg_commit() { asm volatile("wgmma.commit_group.sync.aligned;" ::: "memory"); }
template <int N> __device__ __forceinline__ void wg_wait() { asm volatile("wgmma.wait_group.sync.aligned %0;" :: "n"(N) : "memory"); }
template <int N> __device__ __forceinline__ void reg_fence(float (&r)[N]) {
#pragma unroll
    for (int i = 0; i < N; i++) asm volatile("" : "+f"(r[i]) :: "memory");
}

#define ACC8(d, o) "+f"(d[o]), "+f"(d[o + 1]), "+f"(d[o + 2]), "+f"(d[o + 3]), "+f"(d[o + 4]), "+f"(d[o + 5]), "+f"(d[o + 6]), "+f"(d[o + 7])
#define ACC32(d, o) ACC8(d, o), ACC8(d, o + 8), ACC8(d, o + 16), ACC8(d, o + 24)
#define REGS32 "{%0, %1, %2, %3, %4, %5, %6, %7, %8, %9, %10, %11, %12, %13, %14, %15, " \
               "%16, %17, %18, %19, %20, %21, %22, %23, %24, %25, %26, %27, %28, %29, %30, %31}"
#define REGS64 "{%0, %1, %2, %3, %4, %5, %6, %7, %8, %9, %10, %11, %12, %13, %14, %15, " \
               "%16, %17, %18, %19, %20, %21, %22, %23, %24, %25, %26, %27, %28, %29, %30, %31, " \
               "%32, %33, %34, %35, %36, %37, %38, %39, %40, %41, %42, %43, %44, %45, %46, %47, " \
               "%48, %49, %50, %51, %52, %53, %54, %55, %56, %57, %58, %59, %60, %61, %62, %63}"

__device__ __forceinline__ void mma_n64_ss_bt(float (&d)[32], uint64_t da, uint64_t db, int accumulate) {
    asm volatile("{\n.reg .pred p;\nsetp.ne.b32 p, %34, 0;\n"
                 "wgmma.mma_async.sync.aligned.m64n64k16.f32.bf16.bf16 " REGS32 ", %32, %33, p, 1, 1, 0, 1;\n}"
                 : ACC32(d, 0) : "l"(da), "l"(db), "r"(accumulate));
}
template <int TB>
__device__ __forceinline__ void mma_n64_rs(float (&d)[32], const uint32_t* a, uint64_t db, int accumulate) {
    asm volatile("{\n.reg .pred p;\nsetp.ne.b32 p, %37, 0;\n"
                 "wgmma.mma_async.sync.aligned.m64n64k16.f32.bf16.bf16 " REGS32 ", {%32, %33, %34, %35}, %36, p, 1, 1, %38;\n}"
                 : ACC32(d, 0) : "r"(a[0]), "r"(a[1]), "r"(a[2]), "r"(a[3]), "l"(db), "r"(accumulate), "n"(TB));
}
__device__ __forceinline__ void mma_n128_rs_bt(float (&d)[64], const uint32_t* a, uint64_t db) {
    asm volatile("{\n.reg .pred p;\nsetp.ne.b32 p, 1, 0;\n"
                 "wgmma.mma_async.sync.aligned.m64n128k16.f32.bf16.bf16 " REGS64 ", {%64, %65, %66, %67}, %68, p, 1, 1, 1;\n}"
                 : ACC32(d, 0), ACC32(d, 32) : "r"(a[0]), "r"(a[1]), "r"(a[2]), "r"(a[3]), "l"(db));
}

__device__ __forceinline__ int pos_k(int p) { return 8 * (p >> 1) + 2 * (p & 1); }
__device__ __forceinline__ int pos_v(int p) { return pos_k(p) + 4; }
__device__ __forceinline__ bool item_is_v(int pos) { return pos & 4; }
__device__ __forceinline__ int item_tile(int pos) { return (pos >> 3) * 4 + (pos & 3); }

template <int V> struct Const { static constexpr int value = V; };
template <int N, int I = 0, typename F> __device__ __forceinline__ void static_for(F&& f) {
    if constexpr (I < N) { f(Const<I>{}); static_for<N, I + 1>(f); }
}

__device__ __forceinline__ unsigned launch_tag(const Scratch* sc, int cta) {
    return (*(const volatile unsigned*)&sc->epoch[cta * 32] + 1u) | 0x80000000u;
}

struct Ring {
    uint32_t base, full, empty;
    __device__ __forceinline__ uint32_t wait(int pos) const {
        const int slot = pos % kSlots;
        mbar_wait(full + 8 * slot, (pos / kSlots) & 1);
        return base + slot * kSlotBytes;
    }
    __device__ __forceinline__ void release(int pos, int lane) const {
        if (lane == 0) mbar_arrive(empty + 8 * (pos % kSlots));
    }
};

__global__ void __launch_bounds__(kThreads, 1)
gqa_block_kernel(const char* __restrict__ x_raw, const char* __restrict__ wq_raw, Scratch* __restrict__ sc,
                 __nv_bfloat16* __restrict__ out, const __grid_constant__ CUtensorMap map_k,
                 const __grid_constant__ CUtensorMap map_v, const __grid_constant__ CUtensorMap map_wo) {
    extern __shared__ __align__(1024) char smem_raw[];
    const int cta = blockIdx.x;
    const int warp = __shfl_sync(0xffffffffu, threadIdx.x >> 5, 0), lane = threadIdx.x & 31;
    const int b = cta >> 3, h = cta & 7;
    const int bg = b >> 3, j = b & 7;

    Ring ring;
    ring.base = smem_u32(smem_raw);
    ring.full = ring.base + kSlots * kSlotBytes;
    ring.empty = ring.full + 8 * kSlots;
    const uint32_t peers_ready = ring.empty + 8 * kSlots;
    const uint32_t q_ready = peers_ready + 8;
    const uint32_t pace = q_ready + 8;
    const uint32_t stats = ring.full + 512;

    uint64_t stream_policy;
    asm volatile("createpolicy.fractional.L2::evict_first.b64 %0, 1.0;" : "=l"(stream_policy));
    if (warp == 8) {
        if (elect_one()) {
#pragma unroll
            for (int i = 0; i < EARLY; i++) mbar_init(ring.full + 8 * i, 1);
            asm volatile("fence.mbarrier_init.release.cluster;" ::: "memory");
#pragma unroll
            for (int i = 0; i < EARLY; i++) {
                mbar_expect_tx(ring.full + 8 * i, kSlotBytes);
                tma_kv(ring.base + i * kSlotBytes, &map_k, cta * 512 + i * 8, ring.full + 8 * i, stream_policy);
            }
            map_prefetch(&map_v);
#pragma unroll
            for (int i = EARLY; i < kSlots; i++) mbar_init(ring.full + 8 * i, 1);
#pragma unroll
            for (int i = 0; i < kSlots; i++) mbar_init(ring.empty + 8 * i, 4);
            mbar_init(peers_ready, 1);
            mbar_init(q_ready, 4);
            asm volatile("st.volatile.shared.v2.u32 [%0], {%1, %2};" :: "r"(pace), "r"(kDepthMain), "r"(0) : "memory");
            asm volatile("fence.mbarrier_init.release.cluster;" ::: "memory");
        }
        __syncwarp();
        asm volatile("bar.arrive 1, %0;" :: "n"(kInitThreads) : "memory");
    }

    if (warp >= 8) {
        asm volatile("setmaxnreg.dec.sync.aligned.u32 40;");
        if (warp == 8) {
            if (elect_one()) {
                int slot = EARLY, lap = 0;
                bool started = false;
                for (int pos = EARLY; pos < kItems; pos++) {
                    const int releases = lap + (slot >= kHeadSlot);
                    if (releases > 0) mbar_wait(ring.empty + 8 * slot, (releases - 1) & 1);
                    if (!started) started = mbar_test(q_ready, 0);
                    int depth;
                    asm volatile("st.volatile.shared.u32 [%0], %1;" :: "r"(pace + 4), "r"(pos) : "memory");
                    asm volatile("ld.volatile.shared.u32 %0, [%1];" : "=r"(depth) : "r"(pace) : "memory");
                    if (!started) depth = pos < PRE_END ? D_PRE : kDepthHead;
                    else if (D_CATCH && pos < 24) depth = D_CATCH;
                    if (pos >= kTailStart) depth = pos < kWoPos ? kDepthTail : (WO_PAT >> (4 * (pos - kWoPos))) & 15;
                    if (pos >= depth) ring.wait(pos - depth);
                    const uint32_t bar = ring.full + 8 * slot, dst = ring.base + slot * kSlotBytes;
                    mbar_expect_tx(bar, kSlotBytes);
                    if (pos < kWoPos) {
                        tma_kv(dst, item_is_v(pos) ? &map_v : &map_k, cta * 512 + item_tile(pos) * 8, bar, stream_policy);
                        if (pos == 100) map_prefetch(&map_wo);
                    } else {
                        tma_2d(dst, &map_wo, j * 64, h * 512 + (pos - kWoPos) * 128, bar);
                    }
                    if (++slot == kSlots) { slot = 0; lap++; }
                }
            }
        } else if (warp == 9) {
            const unsigned epoch = launch_tag(sc, cta);
            const int peer = (lane & 8) ? b * 8 + (lane & 7) : (bg * 8 + (lane & 7)) * 8 + h;
            asm volatile("bar.sync 1, %0;" :: "n"(kInitThreads) : "memory");
            asm volatile("bar.sync 3, 288;" ::: "memory");
            if (lane == 0) {
                asm volatile("fence.acq_rel.gpu;" ::: "memory");
                asm volatile("st.relaxed.gpu.global.u32 [%0], %1;" :: "l"(&sc->flag[cta * 32]), "r"(epoch) : "memory");
                sc->epoch[cta * 32] = epoch;
                if (cta == 0) sc->progress[((epoch & 1) ^ 1) * 32] = 0;
            }
            __syncwarp();
            unsigned v;
            int it = 0;
            do {
                __nanosleep(500);
                asm volatile("ld.acquire.gpu.global.u32 %0, [%1];" : "=r"(v) : "l"(&sc->flag[peer * 32]) : "memory");
            } while (v != epoch && ++it < kPollLimit);
            __syncwarp();
            if (lane == 0) mbar_arrive(peers_ready);
        } else if (warp == 10) {
            const unsigned epoch = launch_tag(sc, cta);
            asm volatile("bar.sync 1, %0;" :: "n"(kInitThreads) : "memory");
            if (lane == 0) {
                int done = 0;
                for (int it = 0; done < kTailStart / kPaceStep && it < kPollLimit; it++) {
                    int pos;
                    asm volatile("ld.volatile.shared.u32 %0, [%1];" : "=r"(pos) : "r"(pace + 4) : "memory");
                    const int now = pos / kPaceStep;
                    if (now > done) {
                        unsigned seen;
                        asm volatile("atom.relaxed.gpu.global.add.u32 %0, [%1], %2;" : "=r"(seen)
                                     : "l"(&sc->progress[(epoch & 1) * 32]), "r"(now - done) : "memory");
                        const int lag = ((int)seen - kCtas / 2 - kCtas * (now - 1)) * kPaceStep;
                        const int depth = kDepthMain + (lag + kPaceGain / 2 + 64 * kPaceGain) / kPaceGain - 64;
                        if (now > 2)
                            asm volatile("st.volatile.shared.u32 [%0], %1;" :: "r"(pace), "r"(min(max(depth, kDepthMin), kDepthMax)) : "memory");
                        done = now;
                    } else {
                        __nanosleep(100);
                    }
                }
            }
        }
    } else {
        TRACE(0);
        const int wg = warp >> 2, wq = warp & 3;
        const int g = lane >> 2, t = lane & 3;
        const bool active = (wq >> 1) == wg;
        const int hp = wq & 1;

        {
            const int tid = threadIdx.x;
            const int xr = tid >> 4, xc = tid & 15, wr = tid >> 3, wc = tid & 7;
            const char* xs = x_raw + (size_t)(bg * 64 + xr) * 1024 + xc * 16;
            const char* ws = wq_raw + (size_t)wr * 8192 + (h * 512 + j * 64) * 2 + wc * 16;
            const uint32_t xd = ring.base + kHeadSlot * kSlotBytes + (xc >> 3) * 8192 + xr * 128 + (((xc ^ xr) & 7) << 4);
            const uint32_t wd = ring.base + (kHeadSlot + 1) * kSlotBytes + wr * 128 + (((wc ^ wr) & 7) << 4);
#pragma unroll
            for (int c = 0; c < 4; c++) {
#pragma unroll
                for (int i = 0; i < 4; i++) {
                    cp_async16(wd + c * 2 * kSlotBytes + i * 4096, ws + (size_t)(c * 128 + i * 32) * 8192);
                    cp_async16(xd + c * 2 * kSlotBytes + i * 2048, xs + i * 16384 + c * 256);
                }
                asm volatile("cp.async.commit_group;" ::: "memory");
            }
        }
        const unsigned epoch = launch_tag(sc, cta);
        uint4* const qx_dst = sc->qx + (((bg * 8 + 2 * wq) * 8 + h) * 8 + j) * 64 + lane;
        const int qx_now = (epoch & 1) * kCtas * 512;
        uint4* const ox_mine = sc->ox + cta * 512 + hp * 256 + lane;
        uint4* const px_dst = sc->px + ((b * 8 + 2 * wq) * 8 + h) * 64 + lane;
        if (WARM_PROBE && wg == 0 && lane >= 32 - WARM_PROBE) {
            st_gpu(qx_dst + qx_now + 32, 0, 0, 0, 0);
            st_gpu(qx_dst + qx_now + 4096 + 32, 0, 0, 0, 0);
        }
        asm volatile("setmaxnreg.inc.sync.aligned.u32 232;");
        asm volatile("bar.sync 1, %0;" :: "n"(kInitThreads) : "memory");

        float s[32];
        auto chunk_landed = [&](auto c) {
            asm volatile("cp.async.wait_group %0;" :: "n"(3 - c.value) : "memory");
            asm volatile("fence.proxy.async.shared::cta;" ::: "memory");
        };
        if (wg == 0) {
            static_for<4>([&](auto c) {
                chunk_landed(c);
                asm volatile("bar.sync %0, 256;" :: "n"(5 + c.value) : "memory");
                LAND(c.value);
                const uint32_t xa = ring.base + (kHeadSlot + 2 * c.value) * kSlotBytes, wa = xa + kSlotBytes;
                const uint64_t xd = make_desc(xa, 16, 1024), wd = make_desc(wa, 16, 1024);
                wg_fence();
#pragma unroll
                for (int ks = 0; ks < 8; ks++)
                    mma_n64_ss_bt(s, advance(xd, (ks >> 2) * 8192 + (ks & 3) * 32), advance(wd, ks * 2048), c.value | ks);
                wg_commit();
                wg_wait<0>();
                ring.release(kHeadSlot + 2 * c.value, lane);
                ring.release(kHeadSlot + 2 * c.value + 1, lane);
            });
            reg_fence(s);
            TRACE(1);
#pragma unroll
            for (int r = 0; r < 2; r++)
#pragma unroll
                for (int c = 0; c < 2; c++) {
                    const float* a = s + 16 * c + 2 * r;
                    st_gpu(qx_dst + qx_now + r * 4096 + c * 32, nonzero(pack_bf16(a[0], a[1])), pack_bf16(a[4], a[5]),
                           nonzero(pack_bf16(a[8], a[9])), pack_bf16(a[12], a[13]));
                }
            asm volatile("bar.arrive 9, 256;" ::: "memory");
        } else {
            static_for<4>([&](auto c) {
                chunk_landed(c);
                asm volatile("bar.arrive %0, 256;" :: "n"(5 + c.value) : "memory");
            });
            asm volatile("bar.sync 9, 256;" ::: "memory");
        }

        uint32_t qa[32];
#pragma unroll
        for (int i = 0; i < 32; i++) qa[i] = 0;
        if (active) {
            const uint4* src = sc->qx + qx_now + (cta * 8 + 4 * hp) * 64 + lane;
            const uint4* probe = sc->qx + qx_now + (cta * 8 + 4 * hp + (lane & 3)) * 64 + 63;
            int it = 0;
            if (X0_PROBE)
                while (!__all_sync(0xffffffffu, lane >= 4 || ld_probe(probe, 2) != 0))
                    if (++it > kPollLimit) break;
            TRACE(9);
            while (true) {
                uint32_t low = 0xffffffffu;
#pragma unroll
                for (int r = 0; r < 2; r++)
#pragma unroll
                    for (int c = 0; c < 4; c++) {
                        const uint4 v = ld_gpu(src + (r * 4 + c) * 32);
                        qa[8 * c + r] = v.x; qa[8 * c + 2 + r] = v.y; qa[8 * c + 4 + r] = v.z; qa[8 * c + 6 + r] = v.w;
                        low = __vimin3_u32(low, v.x, v.z);
                    }
                if (__all_sync(0xffffffffu, low != 0)) break;
                if (++it > kPollLimit) break;
            }
            if (lane == 0) mbar_arrive(q_ready);
        }
        TRACE(2);

        const float kScale = 0.08838834764831845f * 1.4426950408889634f;
        float o[64];
#pragma unroll
        for (int i = 0; i < 64; i++) o[i] = 0.f;
        uint32_t pa[16];
#pragma unroll
        for (int i = 0; i < 16; i++) pa[i] = 0;
        float m0 = -INFINITY, m1 = -INFINITY, l0 = 0.f, l1 = 0.f;

        auto issue_qk = [&](int pos, float (&s)[32]) {
            const uint64_t kd = make_desc(ring.wait(pos), 16, 2048);
            wg_fence();
#pragma unroll
            for (int ks = 0; ks < 8; ks++) mma_n64_rs<0>(s, qa + 4 * ks, advance(kd, (ks >> 2) * 1024 + (ks & 3) * 32), ks);
            wg_commit();
        };
        auto issue_pv = [&](int pos, const uint32_t (&pf)[16]) {
            const uint64_t vd = make_desc(ring.wait(pos), 1024, 2048);
            wg_fence();
#pragma unroll
            for (int ks = 0; ks < 4; ks++) mma_n128_rs_bt(o, pf + 4 * ks, advance(vd, ks * 4096));
            wg_commit();
        };
        float alpha0 = 1.f, alpha1 = 1.f;
        auto softmax = [&](float (&s)[32]) {
            float x0 = fmaxf(s[0], s[1]), x1 = fmaxf(s[2], s[3]);
#pragma unroll
            for (int i = 1; i < 8; i++) {
                x0 = fmaxf(x0, fmaxf(s[4 * i], s[4 * i + 1]));
                x1 = fmaxf(x1, fmaxf(s[4 * i + 2], s[4 * i + 3]));
            }
            x0 = fmaxf(x0, __shfl_xor_sync(0xffffffffu, x0, 1));
            x1 = fmaxf(x1, __shfl_xor_sync(0xffffffffu, x1, 1));
            x0 = fmaxf(x0, __shfl_xor_sync(0xffffffffu, x0, 2));
            x1 = fmaxf(x1, __shfl_xor_sync(0xffffffffu, x1, 2));
            const float n0 = fmaxf(m0, x0), n1 = fmaxf(m1, x1);
            alpha0 = ex2((m0 - n0) * kScale);
            alpha1 = ex2((m1 - n1) * kScale);
            m0 = n0; m1 = n1;
            const float b0 = -n0 * kScale, b1 = -n1 * kScale;
            float r0 = 0.f, r1 = 0.f;
#pragma unroll
            for (int i = 0; i < 8; i++) {
                s[4 * i] = ex2(fmaf(s[4 * i], kScale, b0));
                s[4 * i + 1] = ex2(fmaf(s[4 * i + 1], kScale, b0));
                s[4 * i + 2] = ex2(fmaf(s[4 * i + 2], kScale, b1));
                s[4 * i + 3] = ex2(fmaf(s[4 * i + 3], kScale, b1));
                r0 += s[4 * i] + s[4 * i + 1];
                r1 += s[4 * i + 2] + s[4 * i + 3];
            }
            l0 = fmaf(l0, alpha0, r0);
            l1 = fmaf(l1, alpha1, r1);
        };
        auto rescale_and_pack = [&]() {
#pragma unroll
            for (int i = 0; i < 16; i++) {
                o[4 * i] *= alpha0; o[4 * i + 1] *= alpha0;
                o[4 * i + 2] *= alpha1; o[4 * i + 3] *= alpha1;
                pa[i] = pack_bf16(s[2 * i], s[2 * i + 1]);
            }
        };

        {
            const int pos = wg;
            issue_qk(pos, s);
            wg_wait<0>();
            reg_fence(s);
            ring.release(pos, lane);
            if (active) { softmax(s); rescale_and_pack(); }
        }
        TRACE(3);
        int vpos = pos_v(0) + wg;
#pragma unroll 1
        for (int p = 1; p < kPairs - 1; p++) {
            const int kpos = pos_k(p) + wg;
            issue_qk(kpos, s);
            issue_pv(vpos, pa);
            wg_wait<1>();
            reg_fence(s);
            ring.release(kpos, lane);
            if (active) softmax(s);
            wg_wait<0>();
            reg_fence(o);
            ring.release(vpos, lane);
            if (active) rescale_and_pack();
            vpos = pos_v(p) + wg;
            if ((unsigned)(p - kArmAt) < 8u) {
                const int c = p - kArmAt;
                {
                    if (wg == 0) { if (c < 4) st_gpu(px_dst + (c >> 1) * 512 + (c & 1) * 32, 0, 0, 0, 0); }
                    else if (active) st_gpu(ox_mine + c * 32, 0, 0, 0, 0);
                }
                if (c == 7) asm volatile("bar.arrive 3, 288;" ::: "memory");
            } else if (wg == 0 && (unsigned)(p - kArmAt - 8) < 4u) {
                const int c = p - kArmAt - 8;
                st_gpu(qx_dst + (kCtas * 512 - qx_now) + (c >> 1) * 4096 + (c & 1) * 32, 0, 0, 0, 0);
            }
        }
        mbar_wait(peers_ready, 0);

        const uint32_t part = ring.base + (pos_k(kPairs - 1) % kSlots) * kSlotBytes + hp * 8192 + lane * 16;
        const uint32_t part_p = ring.base + (pos_k(kPairs - 2) % kSlots) * kSlotBytes + hp * 2048 + lane * 16;
        float s2[32];
        uint32_t pb[16];
#pragma unroll
        for (int i = 0; i < 16; i++) pb[i] = 0;
        issue_qk(pos_k(kPairs - 1) + wg, s2);
        wg_wait<0>();
        reg_fence(s2);
        if (active) {
            softmax(s2);
            l0 += __shfl_xor_sync(0xffffffffu, l0, 1);
            l1 += __shfl_xor_sync(0xffffffffu, l1, 1);
            l0 += __shfl_xor_sync(0xffffffffu, l0, 2);
            l1 += __shfl_xor_sync(0xffffffffu, l1, 2);
            sts128(stats + ((wg * 2 + hp) * 32 + lane) * 16, __float_as_uint(m0), __float_as_uint(m1), __float_as_uint(l0), __float_as_uint(l1));
            asm volatile("bar.sync 10, 128;" ::: "memory");
            const uint4 st = lds128(stats + (((wg ^ 1) * 2 + hp) * 32 + lane) * 16);
            const float pm0 = __uint_as_float(st.x), pm1 = __uint_as_float(st.y);
            const float n0 = fmaxf(m0, pm0), n1 = fmaxf(m1, pm1);
            float f0 = ex2((m0 - n0) * kScale), f1 = ex2((m1 - n1) * kScale);
            f0 /= l0 * f0 + __uint_as_float(st.z) * ex2((pm0 - n0) * kScale);
            f1 /= l1 * f1 + __uint_as_float(st.w) * ex2((pm1 - n1) * kScale);
            alpha0 *= f0;
            alpha1 *= f1;
#pragma unroll
            for (int i = 0; i < 8; i++) {
                pb[2 * i] = pack_bf16(s2[4 * i] * f0, s2[4 * i + 1] * f0);
                pb[2 * i + 1] = pack_bf16(s2[4 * i + 2] * f1, s2[4 * i + 3] * f1);
                s[4 * i] *= alpha0; s[4 * i + 1] *= alpha0;
                s[4 * i + 2] *= alpha1; s[4 * i + 3] *= alpha1;
            }
            rescale_and_pack();
        }

        if (wg == 0) {
            if (active) {
#pragma unroll
                for (int c = 0; c < 4; c++) sts128(part_p + c * 512, pb[4 * c], pb[4 * c + 1], pb[4 * c + 2], pb[4 * c + 3]);
                asm volatile("bar.arrive 12, 128;" ::: "memory");
            }
            issue_pv(vpos, pa);
            wg_wait<0>();
            reg_fence(o);
            if (active) {
#pragma unroll
                for (int c = 0; c < 16; c++)
                    sts128(part + c * 512, __float_as_uint(o[4 * c]), __float_as_uint(o[4 * c + 1]),
                           __float_as_uint(o[4 * c + 2]), __float_as_uint(o[4 * c + 3]));
                asm volatile("bar.arrive 4, 128;" ::: "memory");
            }
            TRACE(4);

            uint32_t oa[128];
#pragma unroll
            for (int i = 0; i < 128; i++) oa[i] = 0;
            {
                const uint4* src = sc->ox + ((bg * 8 + 2 * wq) * 8 + h) * 512 + lane;
                const uint4* probe = sc->ox + ((bg * 8 + 2 * wq + ((lane >> 1) & 1)) * 8 + h) * 512 + (lane & 1) * 256 + PROBE_CHUNK * 32 + 31;
                uint32_t pending = 3;
                int it = 0;
                while (true) {
                    uint32_t seen = __ballot_sync(0xffffffffu, lane < 4 && ld_probe(probe, 2) != 0);
                    seen = ((seen & 3) == 3) | ((seen >> 2) == 3) << 1;
                    if (BOTH && (pending & seen) == 3) {
                        uint32_t low0 = 0xffffffffu, low1 = 0xffffffffu;
#pragma unroll
                        for (int c = 0; c < 16; c++)
#pragma unroll
                            for (int r = 0; r < 2; r++) {
                                const uint4 v = ld_gpu(src + r * 8 * 512 + c * 32);
                                oa[8 * c + r] = v.x; oa[8 * c + 2 + r] = v.y; oa[8 * c + 4 + r] = v.z; oa[8 * c + 6 + r] = v.w;
                            }
#pragma unroll
                        for (int c = 0; c < 16; c++) {
                            low0 = __vimin3_u32(low0, oa[8 * c], oa[8 * c + 4]);
                            low1 = __vimin3_u32(low1, oa[8 * c + 1], oa[8 * c + 5]);
                        }
                        pending = (__any_sync(0xffffffffu, low0 == 0) ? 1u : 0u) | (__any_sync(0xffffffffu, low1 == 0) ? 2u : 0u);
                        seen = 0;
                    }
#pragma unroll
                    for (int r = 0; r < 2; r++) {
                        if ((pending & seen) >> r & 1) {
                            uint32_t low = 0xffffffffu;
#pragma unroll
                            for (int c = 0; c < 16; c++) {
                                const uint4 v = ld_gpu(src + r * 8 * 512 + c * 32);
                                oa[8 * c + r] = v.x; oa[8 * c + 2 + r] = v.y; oa[8 * c + 4 + r] = v.z; oa[8 * c + 6 + r] = v.w;
                            }
#pragma unroll
                            for (int c = 0; c < 16; c++) low = __vimin3_u32(low, oa[8 * c + r], oa[8 * c + 4 + r]);
                            if (__all_sync(0xffffffffu, low != 0)) pending &= ~(1u << r);
                        }
                    }
                    if (pending == 0) break;
                    if (++it > kPollLimit) break;
                }
            }
            TRACE(6);

#pragma unroll
            for (int c = 0; c < 4; c++) {
                const uint64_t wd = make_desc(ring.wait(kWoPos + c), 16, 1024);
                wg_fence();
#pragma unroll
                for (int ks = 0; ks < 8; ks++) mma_n64_rs<1>(s, oa + 32 * c + 4 * ks, advance(wd, ks * 2048), c | ks);
                wg_commit();
            }
            wg_wait<0>();
            reg_fence(s);
            TRACE(7);
#pragma unroll
            for (int r = 0; r < 2; r++)
#pragma unroll
                for (int c = 0; c < 2; c++) {
                    const float* a = s + 16 * c + 2 * r;
                    st_gpu(px_dst + r * 512 + c * 32, nonzero(pack_bf16(a[0], a[1])), pack_bf16(a[4], a[5]),
                           nonzero(pack_bf16(a[8], a[9])), pack_bf16(a[12], a[13]));
                }
        } else {
            uint32_t pc[16];
#pragma unroll
            for (int i = 0; i < 16; i++) pc[i] = 0;
            if (active) {
                asm volatile("bar.sync 12, 128;" ::: "memory");
#pragma unroll
                for (int c = 0; c < 4; c++) {
                    const uint4 v = lds128(part_p + c * 512);
                    pc[4 * c] = v.x; pc[4 * c + 1] = v.y; pc[4 * c + 2] = v.z; pc[4 * c + 3] = v.w;
                }
            }
            issue_pv(vpos, pa);
            issue_pv(pos_v(kPairs - 1), pc);
            issue_pv(pos_v(kPairs - 1) + 1, pb);
            uint4 other[16];
            if (active) {
                asm volatile("bar.sync 4, 128;" ::: "memory");
#pragma unroll
                for (int c = 0; c < 16; c++) other[c] = lds128(part + c * 512);
            }
            wg_wait<0>();
            reg_fence(o);
            TRACE1(11);
            if (active) {
                uint32_t w[32];
#pragma unroll
                for (int i = 0; i < 16; i++) {
                    w[i] = pack_bf16(o[4 * i] + __uint_as_float(other[i].x), o[4 * i + 1] + __uint_as_float(other[i].y));
                    w[16 + i] = pack_bf16(o[4 * i + 2] + __uint_as_float(other[i].z), o[4 * i + 3] + __uint_as_float(other[i].w));
                }
#pragma unroll
                for (int c = 0; c < 8; c++)
                    st_gpu(ox_mine + c * 32, nonzero(w[4 * c]), w[4 * c + 1], nonzero(w[4 * c + 2]), w[4 * c + 3]);
            }
            TRACE1(5);

            if (wq < 2) {
                const uint4* src = sc->px + cta * 512 + wq * 32 + lane;
                const uint4* probe = sc->px + cta * 512 + (lane & 7) * 64 + wq * 32 + 31;
                uint4 v[8];
                int it = 0;
                while (!__any_sync(0xffffffffu, lane < 8 && ld_probe(probe, 2) != 0))
                    if (++it > kPollLimit) break;
#pragma unroll
                for (int i = 0; i < 8; i++) v[i] = make_uint4(0, 0, 0, 0);
                while (true) {
                    uint32_t low = 0xffffffffu;
#pragma unroll
                    for (int i = 0; i < 8; i++) if (v[i].x == 0 || v[i].z == 0) v[i] = ld_gpu(src + i * 64);
#pragma unroll
                    for (int i = 0; i < 8; i++) low = __vimin3_u32(low, v[i].x, v[i].z);
                    if (low != 0) break;
                    if (++it > kPollLimit) break;
                }
                float r[8];
#pragma unroll
                for (int q = 0; q < 8; q++) r[q] = 0.f;
#pragma unroll
                for (int i = 0; i < 8; i++) {
                    const uint32_t w[4] = {v[i].x, v[i].y, v[i].z, v[i].w};
#pragma unroll
                    for (int q = 0; q < 4; q++) {
                        r[2 * q] += __uint_as_float(w[q] << 16);
                        r[2 * q + 1] += __uint_as_float(w[q] & 0xffff0000u);
                    }
                }
                uint32_t* dst = reinterpret_cast<uint32_t*>(out + ((bg * 8 + h) * 8 + g) * 512 + j * 64 + wq * 32 + 2 * t);
#pragma unroll
                for (int q = 0; q < 4; q++) dst[4 * q] = pack_bf16(r[2 * q], r[2 * q + 1]);
            }
            TRACE1(8);
        }
    }
}

typedef CUresult (*EncodeTiledFn)(CUtensorMap*, CUtensorMapDataType, cuuint32_t, void*, const cuuint64_t*, const cuuint64_t*,
                                  const cuuint32_t*, const cuuint32_t*, CUtensorMapInterleave, CUtensorMapSwizzle,
                                  CUtensorMapL2promotion, CUtensorMapFloatOOBfill);

void encode_2d(EncodeTiledFn fn, CUtensorMap* map, void* base, uint64_t cols, uint64_t rows, uint32_t box_rows) {
    const cuuint64_t dims[2] = {cols, rows};
    const cuuint64_t strides[1] = {cols * 2};
    const cuuint32_t box[2] = {64, box_rows};
    const cuuint32_t elem[2] = {1, 1};
    fn(map, CU_TENSOR_MAP_DATA_TYPE_BFLOAT16, 2, base, dims, strides, box, elem, CU_TENSOR_MAP_INTERLEAVE_NONE,
       CU_TENSOR_MAP_SWIZZLE_128B, (CUtensorMapL2promotion)WO_PROMO, CU_TENSOR_MAP_FLOAT_OOB_FILL_NONE);
}

void encode_kv(EncodeTiledFn fn, CUtensorMap* map, void* base) {
    const cuuint64_t dims[4] = {64, 8, 2, 65536};
    const cuuint64_t strides[3] = {256, 128, 2048};
    const cuuint32_t box[4] = {64, 8, 2, 8};
    const cuuint32_t elem[4] = {1, 1, 1, 1};
    fn(map, CU_TENSOR_MAP_DATA_TYPE_BFLOAT16, 4, base, dims, strides, box, elem, CU_TENSOR_MAP_INTERLEAVE_NONE,
       CU_TENSOR_MAP_SWIZZLE_128B, (CUtensorMapL2promotion)KV_PROMO, CU_TENSOR_MAP_FLOAT_OOB_FILL_NONE);
}

}

extern "C" void kernel_launch(void* const* d_in, const int* in_sizes, int n_in, void* d_out, int out_size) {
    (void)in_sizes; (void)n_in; (void)out_size;
    static EncodeTiledFn encode = nullptr;
    static Scratch* scratch = nullptr;
    if (!encode) {
        cudaGetSymbolAddress((void**)&scratch, g_scratch);
        void* fn = nullptr;
        cudaDriverEntryPointQueryResult status;
        cudaGetDriverEntryPoint("cuTensorMapEncodeTiled", &fn, cudaEnableDefault, &status);
        encode = (EncodeTiledFn)fn;
        cudaFuncSetAttribute(gqa_block_kernel, cudaFuncAttributeMaxDynamicSharedMemorySize, kSmemBytes);
    }
    CUtensorMap map_k, map_v, map_wo;
    encode_kv(encode, &map_k, d_in[1]);
    encode_kv(encode, &map_v, d_in[2]);
    encode_2d(encode, &map_wo, d_in[4], 512, 4096, 128);
    gqa_block_kernel<<<kCtas, kThreads, kSmemBytes>>>((const char*)d_in[0], (const char*)d_in[3], scratch,
                                                      (__nv_bfloat16*)d_out, map_k, map_v, map_wo);
}
```

```cpp
#include <cuda_runtime.h>
#include <cuda_bf16.h>
#include <cuda.h>
#include <stdint.h>

namespace {

constexpr int kCtas = 128;
constexpr int kThreads = 384;
constexpr int kInitThreads = 352;
constexpr int kSlots = 14;
constexpr int kSlotBytes = 16384;
constexpr int kPairs = 32;
constexpr int kHeadSlot = 6;
constexpr int kWoPos = 4 * kPairs;
constexpr int kItems = kWoPos + 4;
constexpr int kSmemBytes = kSlots * kSlotBytes + 512 + 2048;
constexpr int kPollLimit = 1 << 16;
constexpr long long kWaitClocks = 1ll << 25;

constexpr int kDepthFirst = 3;
constexpr int kDepthHead = 4;
constexpr int kDepthMain = 3, kDepthMin = 2, kDepthMax = 4;
constexpr int kTailStart = 126, kDepthTail = 2;
constexpr int kPaceStep = 2;
constexpr int kPaceGain = 96;
constexpr int kArmAt = 8;
constexpr int kConsumerRegs = 232, kHelperRegs = 40;
static_assert(8 * kConsumerRegs + 4 * kHelperRegs <= 12 * 168, "setmaxnreg must stay within the launch allocation");

struct Scratch {
    uint4 qx[2 * kCtas * 512];
    uint4 ox[kCtas * 512];
    uint4 px[kCtas * 512];
    unsigned flag[kCtas * 32];
    unsigned epoch[kCtas * 32];
    unsigned progress[2 * 32];
};
__device__ Scratch g_scratch;

__device__ __forceinline__ uint32_t smem_u32(const void* p) { return (uint32_t)__cvta_generic_to_shared(p); }

__device__ __forceinline__ bool elect_one() {
    uint32_t p;
    asm volatile("{\n.reg .pred q;\nelect.sync _|q, 0xffffffff;\nselp.u32 %0, 1, 0, q;\n}" : "=r"(p));
    return p != 0;
}
__device__ __forceinline__ void mbar_init(uint32_t bar, int count) {
    asm volatile("mbarrier.init.shared::cta.b64 [%0], %1;" :: "r"(bar), "r"(count) : "memory");
}
__device__ __forceinline__ void mbar_expect_tx(uint32_t bar, int bytes) {
    asm volatile("mbarrier.arrive.expect_tx.shared::cta.b64 _, [%0], %1;" :: "r"(bar), "r"(bytes) : "memory");
}
__device__ __forceinline__ void mbar_arrive(uint32_t bar) {
    asm volatile("mbarrier.arrive.shared::cta.b64 _, [%0];" :: "r"(bar) : "memory");
}
__device__ __forceinline__ bool mbar_try(uint32_t bar, uint32_t parity) {
    uint32_t ok;
    asm volatile("{\n.reg .pred p;\nmbarrier.try_wait.parity.shared::cta.b64 p, [%1], %2;\nselp.u32 %0, 1, 0, p;\n}"
                 : "=r"(ok) : "r"(bar), "r"(parity) : "memory");
    return ok != 0;
}
__device__ __forceinline__ bool mbar_test(uint32_t bar, uint32_t parity) {
    uint32_t ok;
    asm volatile("{\n.reg .pred p;\nmbarrier.test_wait.parity.shared::cta.b64 p, [%1], %2;\nselp.u32 %0, 1, 0, p;\n}"
                 : "=r"(ok) : "r"(bar), "r"(parity) : "memory");
    return ok != 0;
}
__device__ __forceinline__ void mbar_wait(uint32_t bar, uint32_t parity) {
    if (mbar_try(bar, parity)) return;
    const long long t0 = clock64();
    while (!mbar_try(bar, parity))
        if (clock64() - t0 > kWaitClocks) break;
}

__device__ __forceinline__ void tma_2d(uint32_t dst, const CUtensorMap* map, int c0, int c1, uint32_t bar) {
    asm volatile("cp.async.bulk.tensor.2d.shared::cluster.global.mbarrier::complete_tx::bytes [%0], [%1, {%3, %4}], [%2];"
                 :: "r"(dst), "l"(map), "r"(bar), "r"(c0), "r"(c1) : "memory");
}
__device__ __forceinline__ void tma_kv(uint32_t dst, const CUtensorMap* map, int row_group, uint32_t bar, uint64_t policy) {
    asm volatile("cp.async.bulk.tensor.4d.shared::cluster.global.mbarrier::complete_tx::bytes.L2::cache_hint [%0], [%1, {%3, %3, %3, %4}], [%2], %5;"
                 :: "r"(dst), "l"(map), "r"(bar), "r"(0), "r"(row_group), "l"(policy) : "memory");
}
__device__ __forceinline__ void cp_async16(uint32_t dst, const void* src) {
    asm volatile("cp.async.cg.shared.global [%0], [%1], 16;" :: "r"(dst), "l"(src) : "memory");
}
__device__ __forceinline__ void map_prefetch(const CUtensorMap* map) {
    asm volatile("prefetch.tensormap [%0];" :: "l"(map) : "memory");
}

__device__ __forceinline__ uint4 ld_gpu(const uint4* p) {
    unsigned long long a, b;
    asm volatile("ld.relaxed.gpu.global.v2.b64 {%0, %1}, [%2];" : "=l"(a), "=l"(b) : "l"(p) : "memory");
    return make_uint4((uint32_t)a, (uint32_t)(a >> 32), (uint32_t)b, (uint32_t)(b >> 32));
}
__device__ __forceinline__ void st_gpu(uint4* p, uint32_t x, uint32_t y, uint32_t z, uint32_t w) {
    const unsigned long long a = (unsigned long long)x | ((unsigned long long)y << 32);
    const unsigned long long b = (unsigned long long)z | ((unsigned long long)w << 32);
    asm volatile("st.relaxed.gpu.global.v2.b64 [%0], {%1, %2};" :: "l"(p), "l"(a), "l"(b) : "memory");
}
__device__ __forceinline__ uint32_t ld_probe(const uint4* p, int word) {
    uint32_t v;
    asm volatile("ld.relaxed.gpu.global.u32 %0, [%1];" : "=r"(v) : "l"(reinterpret_cast<const uint32_t*>(p) + word) : "memory");
    return v;
}
__device__ __forceinline__ void sts128(uint32_t addr, uint32_t x, uint32_t y, uint32_t z, uint32_t w) {
    asm volatile("st.shared.v4.u32 [%0], {%1, %2, %3, %4};" :: "r"(addr), "r"(x), "r"(y), "r"(z), "r"(w) : "memory");
}
__device__ __forceinline__ uint4 lds128(uint32_t addr) {
    uint4 v;
    asm volatile("ld.shared.v4.u32 {%0, %1, %2, %3}, [%4];" : "=r"(v.x), "=r"(v.y), "=r"(v.z), "=r"(v.w) : "r"(addr) : "memory");
    return v;
}
__device__ __forceinline__ uint32_t nonzero(uint32_t w) { return w == 0u ? 0x80000000u : w; }

__device__ __forceinline__ uint32_t pack_bf16(float lo, float hi) {
    uint32_t r;
    asm("cvt.rn.bf16x2.f32 %0, %1, %2;" : "=r"(r) : "f"(hi), "f"(lo));
    return r;
}
__device__ __forceinline__ float ex2(float x) {
    float y;
    asm("ex2.approx.ftz.f32 %0, %1;" : "=f"(y) : "f"(x));
    return y;
}

__device__ __forceinline__ uint64_t make_desc(uint32_t addr, uint32_t lbo_bytes, uint32_t sbo_bytes) {
    return (uint64_t)((addr & 0x3FFFF) >> 4) | ((uint64_t)(lbo_bytes >> 4) << 16) | ((uint64_t)(sbo_bytes >> 4) << 32) | (1ull << 62);
}
__device__ __forceinline__ uint64_t advance(uint64_t desc, uint32_t bytes) {
    return (desc & 0xFFFFFFFF00000000ull) | (uint32_t)((uint32_t)desc + (bytes >> 4));
}

__device__ __forceinline__ void wg_fence() { asm volatile("wgmma.fence.sync.aligned;" ::: "memory"); }
__device__ __forceinline__ void wg_commit() { asm volatile("wgmma.commit_group.sync.aligned;" ::: "memory"); }
template <int N> __device__ __forceinline__ void wg_wait() { asm volatile("wgmma.wait_group.sync.aligned %0;" :: "n"(N) : "memory"); }
template <int N> __device__ __forceinline__ void reg_fence(float (&r)[N]) {
#pragma unroll
    for (int i = 0; i < N; i++) asm volatile("" : "+f"(r[i]) :: "memory");
}

#define ACC8(d, o) "+f"(d[o]), "+f"(d[o + 1]), "+f"(d[o + 2]), "+f"(d[o + 3]), "+f"(d[o + 4]), "+f"(d[o + 5]), "+f"(d[o + 6]), "+f"(d[o + 7])
#define ACC32(d, o) ACC8(d, o), ACC8(d, o + 8), ACC8(d, o + 16), ACC8(d, o + 24)
#define REGS32 "{%0, %1, %2, %3, %4, %5, %6, %7, %8, %9, %10, %11, %12, %13, %14, %15, " \
               "%16, %17, %18, %19, %20, %21, %22, %23, %24, %25, %26, %27, %28, %29, %30, %31}"
#define REGS64 "{%0, %1, %2, %3, %4, %5, %6, %7, %8, %9, %10, %11, %12, %13, %14, %15, " \
               "%16, %17, %18, %19, %20, %21, %22, %23, %24, %25, %26, %27, %28, %29, %30, %31, " \
               "%32, %33, %34, %35, %36, %37, %38, %39, %40, %41, %42, %43, %44, %45, %46, %47, " \
               "%48, %49, %50, %51, %52, %53, %54, %55, %56, %57, %58, %59, %60, %61, %62, %63}"

__device__ __forceinline__ void mma_n64_ss_bt(float (&d)[32], uint64_t da, uint64_t db, int accumulate) {
    asm volatile("{\n.reg .pred p;\nsetp.ne.b32 p, %34, 0;\n"
                 "wgmma.mma_async.sync.aligned.m64n64k16.f32.bf16.bf16 " REGS32 ", %32, %33, p, 1, 1, 0, 1;\n}"
                 : ACC32(d, 0) : "l"(da), "l"(db), "r"(accumulate));
}
template <int TB>
__device__ __forceinline__ void mma_n64_rs(float (&d)[32], const uint32_t* a, uint64_t db, int accumulate) {
    asm volatile("{\n.reg .pred p;\nsetp.ne.b32 p, %37, 0;\n"
                 "wgmma.mma_async.sync.aligned.m64n64k16.f32.bf16.bf16 " REGS32 ", {%32, %33, %34, %35}, %36, p, 1, 1, %38;\n}"
                 : ACC32(d, 0) : "r"(a[0]), "r"(a[1]), "r"(a[2]), "r"(a[3]), "l"(db), "r"(accumulate), "n"(TB));
}
__device__ __forceinline__ void mma_n128_rs_bt(float (&d)[64], const uint32_t* a, uint64_t db) {
    asm volatile("{\n.reg .pred p;\nsetp.ne.b32 p, 1, 0;\n"
                 "wgmma.mma_async.sync.aligned.m64n128k16.f32.bf16.bf16 " REGS64 ", {%64, %65, %66, %67}, %68, p, 1, 1, 1;\n}"
                 : ACC32(d, 0), ACC32(d, 32) : "r"(a[0]), "r"(a[1]), "r"(a[2]), "r"(a[3]), "l"(db));
}

__device__ __forceinline__ int pos_k(int p) { return 8 * (p >> 1) + 2 * (p & 1); }
__device__ __forceinline__ int pos_v(int p) { return pos_k(p) + 4; }
__device__ __forceinline__ bool item_is_v(int pos) { return pos & 4; }
__device__ __forceinline__ int item_tile(int pos) { return (pos >> 3) * 4 + (pos & 3); }

template <int V> struct Const { static constexpr int value = V; };
template <int N, int I = 0, typename F> __device__ __forceinline__ void static_for(F&& f) {
    if constexpr (I < N) { f(Const<I>{}); static_for<N, I + 1>(f); }
}

__device__ __forceinline__ unsigned launch_tag(const Scratch* sc, int cta) {
    return (*(const volatile unsigned*)&sc->epoch[cta * 32] + 1u) | 0x80000000u;
}

struct Ring {
    uint32_t base, full, empty;
    __device__ __forceinline__ uint32_t wait(int pos) const {
        const int slot = pos % kSlots;
        mbar_wait(full + 8 * slot, (pos / kSlots) & 1);
        return base + slot * kSlotBytes;
    }
    __device__ __forceinline__ void release(int pos, int lane) const {
        if (lane == 0) mbar_arrive(empty + 8 * (pos % kSlots));
    }
};

__global__ void __launch_bounds__(kThreads, 1)
gqa_block_kernel(const char* __restrict__ x_raw, const char* __restrict__ wq_raw, Scratch* __restrict__ sc,
                 __nv_bfloat16* __restrict__ out, const __grid_constant__ CUtensorMap map_k,
                 const __grid_constant__ CUtensorMap map_v, const __grid_constant__ CUtensorMap map_wo) {
    extern __shared__ __align__(1024) char smem_raw[];
    const int cta = blockIdx.x;
    const int warp = __shfl_sync(0xffffffffu, threadIdx.x >> 5, 0), lane = threadIdx.x & 31;
    const int b = cta >> 3, h = cta & 7;
    const int bg = b >> 3, j = b & 7;

    Ring ring;
    ring.base = smem_u32(smem_raw);
    ring.full = ring.base + kSlots * kSlotBytes;
    ring.empty = ring.full + 8 * kSlots;
    const uint32_t peers_ready = ring.empty + 8 * kSlots;
    const uint32_t q_ready = peers_ready + 8;
    const uint32_t gathered = q_ready + 8;
    const uint32_t pace = gathered + 8;
    const uint32_t stats = ring.full + 512;

    if (warp < 8) {
        const int tid = threadIdx.x;
        const int xr = tid >> 4, xc = tid & 15, wr = tid >> 3, wc = tid & 7;
        const char* xs = x_raw + (size_t)(bg * 64 + xr) * 1024 + xc * 16;
        const char* ws = wq_raw + (size_t)wr * 8192 + (h * 512 + j * 64) * 2 + wc * 16;
        const uint32_t xd = ring.base + kHeadSlot * kSlotBytes + (xc >> 3) * 8192 + xr * 128 + (((xc ^ xr) & 7) << 4);
        const uint32_t wd = ring.base + (kHeadSlot + 1) * kSlotBytes + wr * 128 + (((wc ^ wr) & 7) << 4);
#pragma unroll
        for (int c = 0; c < 4; c++) {
#pragma unroll
            for (int i = 0; i < 4; i++) {
                cp_async16(wd + c * 2 * kSlotBytes + i * 4096, ws + (size_t)(c * 128 + i * 32) * 8192);
                cp_async16(xd + c * 2 * kSlotBytes + i * 2048, xs + i * 16384 + c * 256);
            }
            asm volatile("cp.async.commit_group;" ::: "memory");
        }
    }

    uint64_t stream_policy;
    asm volatile("createpolicy.fractional.L2::evict_first.b64 %0, 1.0;" : "=l"(stream_policy));
    if (warp == 8) {
        if (elect_one()) {
#pragma unroll
            for (int i = 0; i < kDepthFirst; i++) mbar_init(ring.full + 8 * i, 1);
            asm volatile("fence.mbarrier_init.release.cluster;" ::: "memory");
#pragma unroll
            for (int i = 0; i < kDepthFirst; i++) {
                mbar_expect_tx(ring.full + 8 * i, kSlotBytes);
                tma_kv(ring.base + i * kSlotBytes, &map_k, cta * 512 + i * 8, ring.full + 8 * i, stream_policy);
            }
            map_prefetch(&map_v);
#pragma unroll
            for (int i = kDepthFirst; i < kSlots; i++) mbar_init(ring.full + 8 * i, 1);
#pragma unroll
            for (int i = 0; i < kSlots; i++) mbar_init(ring.empty + 8 * i, 4);
            mbar_init(peers_ready, 1);
            mbar_init(q_ready, 4);
            mbar_init(gathered, 4);
            asm volatile("st.volatile.shared.v2.u32 [%0], {%1, %2};" :: "r"(pace), "r"(kDepthMain), "r"(0) : "memory");
            asm volatile("fence.mbarrier_init.release.cluster;" ::: "memory");
        }
        __syncwarp();
        asm volatile("bar.arrive 1, %0;" :: "n"(kInitThreads) : "memory");
    }

    if (warp >= 8) {
        asm volatile("setmaxnreg.dec.sync.aligned.u32 %0;" :: "n"(kHelperRegs));
        if (warp == 8) {
            if (elect_one()) {
                int slot = kDepthFirst, lap = 0;
                bool started = false;
                for (int pos = kDepthFirst; pos < kItems; pos++) {
                    const int releases = lap + (slot >= kHeadSlot);
                    if (releases > 0) mbar_wait(ring.empty + 8 * slot, (releases - 1) & 1);
                    if (!started) started = mbar_test(q_ready, 0);
                    int depth;
                    asm volatile("st.volatile.shared.u32 [%0], %1;" :: "r"(pace + 4), "r"(pos) : "memory");
                    asm volatile("ld.volatile.shared.u32 %0, [%1];" : "=r"(depth) : "r"(pace) : "memory");
                    if (!started) depth = pos < kHeadSlot ? kDepthFirst : kDepthHead;
                    if (pos >= kTailStart) depth = pos < kWoPos ? kDepthTail : 1;
                    if (pos == kItems - 1) mbar_wait(gathered, 0);
                    else ring.wait(pos - depth);
                    const uint32_t bar = ring.full + 8 * slot, dst = ring.base + slot * kSlotBytes;
                    mbar_expect_tx(bar, kSlotBytes);
                    if (pos < kWoPos) {
                        tma_kv(dst, item_is_v(pos) ? &map_v : &map_k, cta * 512 + item_tile(pos) * 8, bar, stream_policy);
                        if (pos == 100) map_prefetch(&map_wo);
                    } else {
                        tma_2d(dst, &map_wo, j * 64, h * 512 + (pos - kWoPos) * 128, bar);
                    }
                    if (++slot == kSlots) { slot = 0; lap++; }
                }
            }
        } else if (warp == 9) {
            const unsigned epoch = launch_tag(sc, cta);
            const int peer = (lane & 8) ? b * 8 + (lane & 7) : (bg * 8 + (lane & 7)) * 8 + h;
            asm volatile("bar.sync 1, %0;" :: "n"(kInitThreads) : "memory");
            asm volatile("bar.sync 3, 288;" ::: "memory");
            if (lane == 0) {
                asm volatile("fence.acq_rel.gpu;" ::: "memory");
                asm volatile("st.relaxed.gpu.global.u32 [%0], %1;" :: "l"(&sc->flag[cta * 32]), "r"(epoch) : "memory");
                sc->epoch[cta * 32] = epoch;
                if (cta == 0) sc->progress[((epoch & 1) ^ 1) * 32] = 0;
            }
            __syncwarp();
            unsigned v;
            int it = 0;
            do {
                __nanosleep(500);
                asm volatile("ld.acquire.gpu.global.u32 %0, [%1];" : "=r"(v) : "l"(&sc->flag[peer * 32]) : "memory");
            } while (v != epoch && ++it < kPollLimit);
            __syncwarp();
            if (lane == 0) mbar_arrive(peers_ready);
        } else if (warp == 10) {
            const unsigned epoch = launch_tag(sc, cta);
            asm volatile("bar.sync 1, %0;" :: "n"(kInitThreads) : "memory");
            if (lane == 0) {
                int done = 0;
                for (int it = 0; done < kTailStart / kPaceStep && it < kPollLimit; it++) {
                    int pos;
                    asm volatile("ld.volatile.shared.u32 %0, [%1];" : "=r"(pos) : "r"(pace + 4) : "memory");
                    const int now = pos / kPaceStep;
                    if (now > done) {
                        unsigned seen;
                        asm volatile("atom.relaxed.gpu.global.add.u32 %0, [%1], %2;" : "=r"(seen)
                                     : "l"(&sc->progress[(epoch & 1) * 32]), "r"(now - done) : "memory");
                        const int lag = ((int)seen - kCtas / 2 - kCtas * (now - 1)) * kPaceStep;
                        const int depth = kDepthMain + (lag + kPaceGain / 2 + 64 * kPaceGain) / kPaceGain - 64;
                        if (now > 2)
                            asm volatile("st.volatile.shared.u32 [%0], %1;" :: "r"(pace), "r"(min(max(depth, kDepthMin), kDepthMax)) : "memory");
                        done = now;
                    } else {
                        __nanosleep(100);
                    }
                }
            }
        }
    } else {
        const int wg = warp >> 2, wq = warp & 3;
        const int g = lane >> 2, t = lane & 3;
        const bool active = (wq >> 1) == wg;
        const int hp = wq & 1;

        const unsigned epoch = launch_tag(sc, cta);
        uint4* const qx_dst = sc->qx + (((bg * 8 + 2 * wq) * 8 + h) * 8 + j) * 64 + lane;
        const int qx_now = (epoch & 1) * kCtas * 512;
        uint4* const ox_mine = sc->ox + cta * 512 + hp * 256 + lane;
        uint4* const px_dst = sc->px + ((b * 8 + 2 * wq) * 8 + h) * 64 + lane;
        asm volatile("setmaxnreg.inc.sync.aligned.u32 %0;" :: "n"(kConsumerRegs));
        asm volatile("bar.sync 1, %0;" :: "n"(kInitThreads) : "memory");

        float s[32];
        auto chunk_landed = [&](auto c) {
            asm volatile("cp.async.wait_group %0;" :: "n"(3 - c.value) : "memory");
            asm volatile("fence.proxy.async.shared::cta;" ::: "memory");
        };
        if (wg == 0) {
            static_for<4>([&](auto c) {
                chunk_landed(c);
                asm volatile("bar.sync %0, 256;" :: "n"(5 + c.value) : "memory");
                const uint32_t xa = ring.base + (kHeadSlot + 2 * c.value) * kSlotBytes, wa = xa + kSlotBytes;
                const uint64_t xd = make_desc(xa, 16, 1024), wd = make_desc(wa, 16, 1024);
                wg_fence();
#pragma unroll
                for (int ks = 0; ks < 8; ks++)
                    mma_n64_ss_bt(s, advance(xd, (ks >> 2) * 8192 + (ks & 3) * 32), advance(wd, ks * 2048), c.value | ks);
                wg_commit();
                wg_wait<0>();
                ring.release(kHeadSlot + 2 * c.value, lane);
                ring.release(kHeadSlot + 2 * c.value + 1, lane);
            });
            reg_fence(s);
#pragma unroll
            for (int r = 0; r < 2; r++)
#pragma unroll
                for (int c = 0; c < 2; c++) {
                    const float* a = s + 16 * c + 2 * r;
                    st_gpu(qx_dst + qx_now + r * 4096 + c * 32, nonzero(pack_bf16(a[0], a[1])), pack_bf16(a[4], a[5]),
                           nonzero(pack_bf16(a[8], a[9])), pack_bf16(a[12], a[13]));
                }
            asm volatile("bar.arrive 9, 256;" ::: "memory");
        } else {
            static_for<4>([&](auto c) {
                chunk_landed(c);
                asm volatile("bar.arrive %0, 256;" :: "n"(5 + c.value) : "memory");
            });
            asm volatile("bar.sync 9, 256;" ::: "memory");
        }

        uint32_t qa[32];
#pragma unroll
        for (int i = 0; i < 32; i++) qa[i] = 0;
        if (active) {
            const uint4* src = sc->qx + qx_now + (cta * 8 + 4 * hp) * 64 + lane;
            const uint4* probe = sc->qx + qx_now + (cta * 8 + 4 * hp + (lane & 3)) * 64 + 63;
            int it = 0;
            while (!__all_sync(0xffffffffu, lane >= 4 || ld_probe(probe, 2) != 0))
                if (++it > kPollLimit) break;
            while (true) {
                uint32_t low = 0xffffffffu;
#pragma unroll
                for (int r = 0; r < 2; r++)
#pragma unroll
                    for (int c = 0; c < 4; c++) {
                        const uint4 v = ld_gpu(src + (r * 4 + c) * 32);
                        qa[8 * c + r] = v.x; qa[8 * c + 2 + r] = v.y; qa[8 * c + 4 + r] = v.z; qa[8 * c + 6 + r] = v.w;
                        low = __vimin3_u32(low, v.x, v.z);
                    }
                if (__all_sync(0xffffffffu, low != 0)) break;
                if (++it > kPollLimit) break;
            }
            if (lane == 0) mbar_arrive(q_ready);
        }

        const float kScale = 0.08838834764831845f * 1.4426950408889634f;
        float o[64];
#pragma unroll
        for (int i = 0; i < 64; i++) o[i] = 0.f;
        uint32_t pa[16];
#pragma unroll
        for (int i = 0; i < 16; i++) pa[i] = 0;
        float m0 = -INFINITY, m1 = -INFINITY, l0 = 0.f, l1 = 0.f;

        auto issue_qk = [&](int pos, float (&s)[32]) {
            const uint64_t kd = make_desc(ring.wait(pos), 16, 2048);
            wg_fence();
#pragma unroll
            for (int ks = 0; ks < 8; ks++) mma_n64_rs<0>(s, qa + 4 * ks, advance(kd, (ks >> 2) * 1024 + (ks & 3) * 32), ks);
            wg_commit();
        };
        auto issue_pv = [&](int pos, const uint32_t (&pf)[16]) {
            const uint64_t vd = make_desc(ring.wait(pos), 1024, 2048);
            wg_fence();
#pragma unroll
            for (int ks = 0; ks < 4; ks++) mma_n128_rs_bt(o, pf + 4 * ks, advance(vd, ks * 4096));
            wg_commit();
        };
        float alpha0 = 1.f, alpha1 = 1.f;
        auto softmax = [&](float (&s)[32]) {
            float x0 = fmaxf(s[0], s[1]), x1 = fmaxf(s[2], s[3]);
#pragma unroll
            for (int i = 1; i < 8; i++) {
                x0 = fmaxf(x0, fmaxf(s[4 * i], s[4 * i + 1]));
                x1 = fmaxf(x1, fmaxf(s[4 * i + 2], s[4 * i + 3]));
            }
            x0 = fmaxf(x0, __shfl_xor_sync(0xffffffffu, x0, 1));
            x1 = fmaxf(x1, __shfl_xor_sync(0xffffffffu, x1, 1));
            x0 = fmaxf(x0, __shfl_xor_sync(0xffffffffu, x0, 2));
            x1 = fmaxf(x1, __shfl_xor_sync(0xffffffffu, x1, 2));
            const float n0 = fmaxf(m0, x0), n1 = fmaxf(m1, x1);
            alpha0 = ex2((m0 - n0) * kScale);
            alpha1 = ex2((m1 - n1) * kScale);
            m0 = n0; m1 = n1;
            float r0 = 0.f, r1 = 0.f;
#pragma unroll
            for (int i = 0; i < 8; i++) {
                s[4 * i] = ex2((s[4 * i] - n0) * kScale);
                s[4 * i + 1] = ex2((s[4 * i + 1] - n0) * kScale);
                s[4 * i + 2] = ex2((s[4 * i + 2] - n1) * kScale);
                s[4 * i + 3] = ex2((s[4 * i + 3] - n1) * kScale);
                r0 += s[4 * i] + s[4 * i + 1];
                r1 += s[4 * i + 2] + s[4 * i + 3];
            }
            l0 = fmaf(l0, alpha0, r0);
            l1 = fmaf(l1, alpha1, r1);
        };
        auto rescale_and_pack = [&]() {
#pragma unroll
            for (int i = 0; i < 16; i++) {
                o[4 * i] *= alpha0; o[4 * i + 1] *= alpha0;
                o[4 * i + 2] *= alpha1; o[4 * i + 3] *= alpha1;
                pa[i] = pack_bf16(s[2 * i], s[2 * i + 1]);
            }
        };

        issue_qk(wg, s);
        wg_wait<0>();
        reg_fence(s);
        ring.release(wg, lane);
        if (active) { softmax(s); rescale_and_pack(); }
        int vpos = pos_v(0) + wg;
#pragma unroll 1
        for (int p = 1; p < kPairs - 1; p++) {
            const int kpos = pos_k(p) + wg;
            issue_qk(kpos, s);
            issue_pv(vpos, pa);
            wg_wait<1>();
            reg_fence(s);
            ring.release(kpos, lane);
            if (active) softmax(s);
            wg_wait<0>();
            reg_fence(o);
            ring.release(vpos, lane);
            if (active) rescale_and_pack();
            vpos = pos_v(p) + wg;
            if ((unsigned)(p - kArmAt) < 8u) {
                const int c = p - kArmAt;
                if (wg == 0 && c < 4) st_gpu(px_dst + (c >> 1) * 512 + (c & 1) * 32, 0, 0, 0, 0);
                if (wg == 1 && active) st_gpu(ox_mine + c * 32, 0, 0, 0, 0);
                if (c == 7) asm volatile("bar.arrive 3, 288;" ::: "memory");
            } else if (wg == 0 && (unsigned)(p - kArmAt - 8) < 4u) {
                const int c = p - kArmAt - 8;
                st_gpu(qx_dst + (kCtas * 512 - qx_now) + (c >> 1) * 4096 + (c & 1) * 32, 0, 0, 0, 0);
            }
        }
        mbar_wait(peers_ready, 0);

        const uint32_t part = ring.base + (pos_k(kPairs - 1) % kSlots) * kSlotBytes + hp * 8192 + lane * 16;
        const uint32_t part_p = ring.base + (pos_k(kPairs - 2) % kSlots) * kSlotBytes + hp * 2048 + lane * 16;
        float s2[32];
        uint32_t pb[16];
#pragma unroll
        for (int i = 0; i < 16; i++) pb[i] = 0;
        issue_qk(pos_k(kPairs - 1) + wg, s2);
        wg_wait<0>();
        reg_fence(s2);
        if (active) {
            softmax(s2);
            l0 += __shfl_xor_sync(0xffffffffu, l0, 1);
            l1 += __shfl_xor_sync(0xffffffffu, l1, 1);
            l0 += __shfl_xor_sync(0xffffffffu, l0, 2);
            l1 += __shfl_xor_sync(0xffffffffu, l1, 2);
            sts128(stats + ((wg * 2 + hp) * 32 + lane) * 16, __float_as_uint(m0), __float_as_uint(m1), __float_as_uint(l0), __float_as_uint(l1));
            asm volatile("bar.sync 10, 128;" ::: "memory");
            const uint4 st = lds128(stats + (((wg ^ 1) * 2 + hp) * 32 + lane) * 16);
            const float pm0 = __uint_as_float(st.x), pm1 = __uint_as_float(st.y);
            const float n0 = fmaxf(m0, pm0), n1 = fmaxf(m1, pm1);
            float f0 = ex2((m0 - n0) * kScale), f1 = ex2((m1 - n1) * kScale);
            f0 /= l0 * f0 + __uint_as_float(st.z) * ex2((pm0 - n0) * kScale);
            f1 /= l1 * f1 + __uint_as_float(st.w) * ex2((pm1 - n1) * kScale);
            alpha0 *= f0;
            alpha1 *= f1;
#pragma unroll
            for (int i = 0; i < 8; i++) {
                pb[2 * i] = pack_bf16(s2[4 * i] * f0, s2[4 * i + 1] * f0);
                pb[2 * i + 1] = pack_bf16(s2[4 * i + 2] * f1, s2[4 * i + 3] * f1);
                s[4 * i] *= alpha0; s[4 * i + 1] *= alpha0;
                s[4 * i + 2] *= alpha1; s[4 * i + 3] *= alpha1;
            }
            rescale_and_pack();
        }

        if (wg == 0) {
            if (active) {
#pragma unroll
                for (int c = 0; c < 4; c++) sts128(part_p + c * 512, pb[4 * c], pb[4 * c + 1], pb[4 * c + 2], pb[4 * c + 3]);
                asm volatile("bar.arrive 12, 128;" ::: "memory");
            }
            issue_pv(vpos, pa);
            wg_wait<0>();
            reg_fence(o);
            if (active) {
#pragma unroll
                for (int c = 0; c < 16; c++)
                    sts128(part + c * 512, __float_as_uint(o[4 * c]), __float_as_uint(o[4 * c + 1]),
                           __float_as_uint(o[4 * c + 2]), __float_as_uint(o[4 * c + 3]));
                asm volatile("bar.arrive 4, 128;" ::: "memory");
            }

            uint32_t oa[128];
#pragma unroll
            for (int i = 0; i < 128; i++) oa[i] = 0;
            {
                const uint4* src = sc->ox + ((bg * 8 + 2 * wq) * 8 + h) * 512 + lane;
                const uint4* probe = sc->ox + ((bg * 8 + 2 * wq + (lane & 1)) * 8 + h) * 512 + 256 + 31;
                uint32_t pending = 3;
                int it = 0;
                while (true) {
                    const uint32_t seen = __ballot_sync(0xffffffffu, lane < 2 && ld_probe(probe, 2) != 0);
#pragma unroll
                    for (int r = 0; r < 2; r++) {
                        if ((pending & seen) >> r & 1) {
#pragma unroll
                            for (int c = 0; c < 16; c++) {
                                const uint4 v = ld_gpu(src + r * 8 * 512 + c * 32);
                                oa[8 * c + r] = v.x; oa[8 * c + 2 + r] = v.y; oa[8 * c + 4 + r] = v.z; oa[8 * c + 6 + r] = v.w;
                            }
                            uint32_t lo[4];
#pragma unroll
                            for (int c = 0; c < 4; c++) lo[c] = min(oa[8 * c + r], oa[8 * c + 4 + r]);
#pragma unroll
                            for (int c = 4; c < 16; c++) lo[c & 3] = __vimin3_u32(lo[c & 3], oa[8 * c + r], oa[8 * c + 4 + r]);
                            const uint32_t low = min(__vimin3_u32(lo[0], lo[1], lo[2]), lo[3]);
                            if (__all_sync(0xffffffffu, low != 0)) pending &= ~(1u << r);
                        }
                    }
                    if (pending == 0) break;
                    if (++it > kPollLimit) break;
                }
            }
            if (lane == 0) mbar_arrive(gathered);

#pragma unroll
            for (int c = 0; c < 4; c++) {
                const uint64_t wd = make_desc(ring.wait(kWoPos + c), 16, 1024);
                wg_fence();
#pragma unroll
                for (int ks = 0; ks < 8; ks++) mma_n64_rs<1>(s, oa + 32 * c + 4 * ks, advance(wd, ks * 2048), c | ks);
                wg_commit();
            }
            wg_wait<0>();
            reg_fence(s);
#pragma unroll
            for (int r = 0; r < 2; r++)
#pragma unroll
                for (int c = 0; c < 2; c++) {
                    const float* a = s + 16 * c + 2 * r;
                    st_gpu(px_dst + r * 512 + c * 32, nonzero(pack_bf16(a[0], a[1])), pack_bf16(a[4], a[5]),
                           nonzero(pack_bf16(a[8], a[9])), pack_bf16(a[12], a[13]));
                }
        } else {
            uint32_t pc[16];
#pragma unroll
            for (int i = 0; i < 16; i++) pc[i] = 0;
            if (active) {
                asm volatile("bar.sync 12, 128;" ::: "memory");
#pragma unroll
                for (int c = 0; c < 4; c++) {
                    const uint4 v = lds128(part_p + c * 512);
                    pc[4 * c] = v.x; pc[4 * c + 1] = v.y; pc[4 * c + 2] = v.z; pc[4 * c + 3] = v.w;
                }
            }
            issue_pv(vpos, pa);
            issue_pv(pos_v(kPairs - 1), pc);
            uint4 other[16];
            if (active) {
                asm volatile("bar.sync 4, 128;" ::: "memory");
#pragma unroll
                for (int c = 0; c < 16; c++) other[c] = lds128(part + c * 512);
            }
            wg_wait<0>();
            reg_fence(o);
            if (active) {
#pragma unroll
                for (int c = 0; c < 16; c++) {
                    o[4 * c] += __uint_as_float(other[c].x); o[4 * c + 1] += __uint_as_float(other[c].y);
                    o[4 * c + 2] += __uint_as_float(other[c].z); o[4 * c + 3] += __uint_as_float(other[c].w);
                }
            }
            issue_pv(pos_v(kPairs - 1) + 1, pb);
            wg_wait<0>();
            reg_fence(o);
            if (active) {
                uint32_t w[32];
#pragma unroll
                for (int i = 0; i < 16; i++) {
                    w[i] = pack_bf16(o[4 * i], o[4 * i + 1]);
                    w[16 + i] = pack_bf16(o[4 * i + 2], o[4 * i + 3]);
                }
#pragma unroll
                for (int c = 0; c < 8; c++)
                    st_gpu(ox_mine + c * 32, nonzero(w[4 * c]), w[4 * c + 1], nonzero(w[4 * c + 2]), w[4 * c + 3]);
            }

            if (wq < 2) {
                const uint4* src = sc->px + cta * 512 + wq * 32 + lane;
                const uint4* probe = sc->px + cta * 512 + (lane & 7) * 64 + wq * 32 + 31;
                uint4 v[8];
                int it = 0;
                while (!__any_sync(0xffffffffu, lane < 8 && ld_probe(probe, 2) != 0))
                    if (++it > kPollLimit) break;
#pragma unroll
                for (int i = 0; i < 8; i++) v[i] = make_uint4(0, 0, 0, 0);
                while (true) {
                    uint32_t low = 0xffffffffu;
#pragma unroll
                    for (int i = 0; i < 8; i++) if (v[i].x == 0 || v[i].z == 0) v[i] = ld_gpu(src + i * 64);
#pragma unroll
                    for (int i = 0; i < 8; i++) low = __vimin3_u32(low, v[i].x, v[i].z);
                    if (low != 0) break;
                    if (++it > kPollLimit) break;
                }
                float r[8];
#pragma unroll
                for (int q = 0; q < 8; q++) r[q] = 0.f;
#pragma unroll
                for (int i = 0; i < 8; i++) {
                    const uint32_t w[4] = {v[i].x, v[i].y, v[i].z, v[i].w};
#pragma unroll
                    for (int q = 0; q < 4; q++) {
                        r[2 * q] += __uint_as_float(w[q] << 16);
                        r[2 * q + 1] += __uint_as_float(w[q] & 0xffff0000u);
                    }
                }
                uint32_t* dst = reinterpret_cast<uint32_t*>(out + ((bg * 8 + h) * 8 + g) * 512 + j * 64 + wq * 32 + 2 * t);
#pragma unroll
                for (int q = 0; q < 4; q++) dst[4 * q] = pack_bf16(r[2 * q], r[2 * q + 1]);
            }
        }
    }
}

typedef CUresult (*EncodeTiledFn)(CUtensorMap*, CUtensorMapDataType, cuuint32_t, void*, const cuuint64_t*, const cuuint64_t*,
                                  const cuuint32_t*, const cuuint32_t*, CUtensorMapInterleave, CUtensorMapSwizzle,
                                  CUtensorMapL2promotion, CUtensorMapFloatOOBfill);

void encode_2d(EncodeTiledFn fn, CUtensorMap* map, void* base, uint64_t cols, uint64_t rows, uint32_t box_rows) {
    const cuuint64_t dims[2] = {cols, rows};
    const cuuint64_t strides[1] = {cols * 2};
    const cuuint32_t box[2] = {64, box_rows};
    const cuuint32_t elem[2] = {1, 1};
    fn(map, CU_TENSOR_MAP_DATA_TYPE_BFLOAT16, 2, base, dims, strides, box, elem, CU_TENSOR_MAP_INTERLEAVE_NONE,
       CU_TENSOR_MAP_SWIZZLE_128B, CU_TENSOR_MAP_L2_PROMOTION_L2_128B, CU_TENSOR_MAP_FLOAT_OOB_FILL_NONE);
}

void encode_kv(EncodeTiledFn fn, CUtensorMap* map, void* base) {
    const cuuint64_t dims[4] = {64, 8, 2, 65536};
    const cuuint64_t strides[3] = {256, 128, 2048};
    const cuuint32_t box[4] = {64, 8, 2, 8};
    const cuuint32_t elem[4] = {1, 1, 1, 1};
    fn(map, CU_TENSOR_MAP_DATA_TYPE_BFLOAT16, 4, base, dims, strides, box, elem, CU_TENSOR_MAP_INTERLEAVE_NONE,
       CU_TENSOR_MAP_SWIZZLE_128B, CU_TENSOR_MAP_L2_PROMOTION_L2_128B, CU_TENSOR_MAP_FLOAT_OOB_FILL_NONE);
}

}

extern "C" void kernel_launch(void* const* d_in, const int* in_sizes, int n_in, void* d_out, int out_size) {
    (void)in_sizes; (void)n_in; (void)out_size;
    static EncodeTiledFn encode = nullptr;
    static Scratch* scratch = nullptr;
    if (!encode) {
        cudaGetSymbolAddress((void**)&scratch, g_scratch);
        void* fn = nullptr;
        cudaDriverEntryPointQueryResult status;
        cudaGetDriverEntryPoint("cuTensorMapEncodeTiled", &fn, cudaEnableDefault, &status);
        encode = (EncodeTiledFn)fn;
        cudaFuncSetAttribute(gqa_block_kernel, cudaFuncAttributeMaxDynamicSharedMemorySize, kSmemBytes);
    }
    CUtensorMap map_k, map_v, map_wo;
    encode_kv(encode, &map_k, d_in[1]);
    encode_kv(encode, &map_v, d_in[2]);
    encode_2d(encode, &map_wo, d_in[4], 512, 4096, 128);
    gqa_block_kernel<<<kCtas, kThreads, kSmemBytes>>>((const char*)d_in[0], (const char*)d_in[3], scratch,
                                                      (__nv_bfloat16*)d_out, map_k, map_v, map_wo);
}
```
